```python
import torch

def _softmax(x, axis=-1):
    return torch.softmax(x, dim=axis)
def _gelu(x):
    return torch.nn.functional.gelu(x, approximate="tanh")
def _silu(x):
    return torch.nn.functional.silu(x)
def _sigmoid(x):
    return torch.sigmoid(x)
def _layernorm(x, axis=-1, eps=1e-5):
    m = x.mean(dim=axis, keepdim=True)
    v = x.var(dim=axis, keepdim=True, unbiased=False)
    return (x - m) / torch.sqrt(v + eps)
def _scatter_add(tgt, idx, src, axis=0):
    return tgt.clone().index_add_(axis, idx, src)
def _segment_sum(src, seg, n):
    out = torch.zeros((n,) + src.shape[1:], dtype=src.dtype)
    return out.index_add_(0, seg, src)
def _pad(x, pw):
    flat = tuple(v for pair in reversed(pw) for v in pair)
    return torch.nn.functional.pad(x, flat)

kernel_name = 'parallel_sum__softmax_full_mha__mixer_channel_mlp__prompt'

def setup_inputs():

    _w = (lambda a: (lambda t: t.to(torch.bfloat16) if t.is_floating_point() else t)(torch.as_tensor(a)))
    def _A_setup():
        B, S, D = 1, 2048, 576
        return {
            "x": _w((lambda *s: torch.randn(*s, dtype=torch.bfloat16) * 0.05)(B, S, D)),
            "wqkv": _w((lambda *s: torch.randn(*s, dtype=torch.bfloat16) * 0.05)(D, 3 * D)),
            "wo": _w((lambda *s: torch.randn(*s, dtype=torch.bfloat16) * 0.05)(D, D)),
        }
    _A_in = _A_setup()

    def _B_setup():
        B, S, D, F = 1, 2048, 576, 4608
        return {
            "x": _w((lambda *s: torch.randn(*s, dtype=torch.bfloat16) * 0.05)(B, S, D)),
            "w1": _w((lambda *s: torch.randn(*s, dtype=torch.bfloat16) * 1.6)(D, F) * (D ** -0.5)),
            "b1": _w((lambda *s: torch.randn(*s, dtype=torch.bfloat16) * 0.8)(F)),
            "w2": _w((lambda *s: torch.randn(*s, dtype=torch.bfloat16) * 0.1)(F, D) * (F ** -0.5)),
            "b2": _w((lambda *s: torch.randn(*s, dtype=torch.bfloat16) * 0.1)(D)),
        }
    _B_in = _B_setup()

    return {
        "A_x": _A_in["x"],
        "A_wqkv": _A_in["wqkv"],
        "A_wo": _A_in["wo"],
        "B_x": _B_in["x"],
        "B_w1": _B_in["w1"],
        "B_b1": _B_in["b1"],
        "B_w2": _B_in["w2"],
        "B_b2": _B_in["b2"],
    }

def reference(A_x, A_wqkv, A_wo, B_x, B_w1, B_b1, B_w2, B_b2):
    def _A_ref(x, wqkv, wo):
        B, S, D = x.shape
        H = 32; Dh = D // H
        qkv = (lambda x, *d: x.permute(*d))((x @ wqkv).reshape(B, S, 3, H, Dh), 2, 0, 3, 1, 4)
        q, k, v = qkv[0], qkv[1], qkv[2]
        scale = Dh ** -0.5
        scores = torch.einsum("bhqd,bhkd->bhqk", q, k) * scale
        p = _softmax(scores, axis=-1)
        o = torch.einsum("bhqk,bhkd->bhqd", p, v)
        return (lambda x, *d: x.permute(*d))(o, 0, 2, 1, 3).reshape(B, S, D) @ wo

    def _B_ref(x, w1, b1, w2, b2):
        y = _layernorm(x, axis=-1)
        h = _gelu(torch.einsum("bsd,df->bsf", y, w1) + b1)
        return torch.einsum("bsf,fd->bsd", h, w2) + b2

    x = A_x
    xn = _layernorm(x, axis=-1)
    return x + _A_ref(xn, A_wqkv, A_wo) + _B_ref(xn, B_w1, B_b1, B_w2, B_b2)
```

```cpp
#include <cuda_runtime.h>
#include <cuda_bf16.h>
#include <cuda.h>
#include <stdint.h>

typedef __nv_bfloat16 bf16;

constexpr int S_ = 2048, D_ = 576, F_ = 4608, H_ = 32, DH_ = 18;
constexpr int NRT = 16;
constexpr int NG = 8;

constexpr int KVB = 10240;
constexpr int QB = 6144;
__device__ __align__(1024) bf16 g_y[S_ * D_];
__device__ __align__(1024) float g_s2[2 * S_];
__device__ __align__(1024) uint8_t g_q[H_ * NRT * QB];
__device__ __align__(1024) uint8_t g_kv[H_ * NRT * KVB];
__device__ __align__(1024) uint8_t g_h[NRT * 72 * 16384];
__device__ __align__(1024) float g_acc[NRT * 9 * 8192];
__device__ __align__(1024) bf16 g_o[S_ * D_];
struct Flags {
  unsigned ln[NRT];
  unsigned zero[NRT];
  unsigned qkv[32];
  unsigned kmax[H_];
  unsigned kcnt[H_];
};
__device__ Flags g_flags;

__device__ __forceinline__ uint32_t smem_u32(const void* p) { return (uint32_t)__cvta_generic_to_shared(p); }
__device__ __forceinline__ void wg_fence() { asm volatile("wgmma.fence.sync.aligned;" ::: "memory"); }
__device__ __forceinline__ void wg_commit() { asm volatile("wgmma.commit_group.sync.aligned;" ::: "memory"); }
template <int N> __device__ __forceinline__ void wg_wait() { asm volatile("wgmma.wait_group.sync.aligned %0;" ::"n"(N) : "memory"); }
template <int N> __device__ __forceinline__ void pin(float (&d)[N]) {
#pragma unroll
  for (int i = 0; i < N; i++) asm volatile("" : "+f"(d[i])::"memory");
}
template <int N> __device__ __forceinline__ void pin(uint32_t (&d)[N]) {
#pragma unroll
  for (int i = 0; i < N; i++) asm volatile("" : "+r"(d[i])::"memory");
}
__device__ __forceinline__ uint64_t mkdesc(uint32_t lo, uint32_t hi) { return ((uint64_t)hi << 32) | lo; }
__host__ __device__ constexpr uint32_t desc_lbo(uint32_t lbo) { return (lbo >> 4) << 16; }
__host__ __device__ constexpr uint32_t desc_hi(uint32_t sbo, uint32_t swz) { return (sbo >> 4) | (swz << 30); }

__device__ __forceinline__ void mbar_init(uint32_t bar, int cnt) { asm volatile("mbarrier.init.shared::cta.b64 [%0], %1;" ::"r"(bar), "r"(cnt)); }
__device__ __forceinline__ void mbar_expect(uint32_t bar, uint32_t bytes) {
  asm volatile("mbarrier.arrive.expect_tx.shared::cta.b64 _, [%0], %1;" ::"r"(bar), "r"(bytes) : "memory");
}
__device__ __forceinline__ void mbar_arrive(uint32_t bar) { asm volatile("mbarrier.arrive.shared::cta.b64 _, [%0];" ::"r"(bar) : "memory"); }
__device__ __forceinline__ bool mbar_try(uint32_t bar, uint32_t ph) {
  uint32_t ok;
  asm volatile("{\n.reg .pred p;\nmbarrier.try_wait.parity.shared::cta.b64 p, [%1], %2;\nselp.u32 %0,1,0,p;\n}" : "=r"(ok) : "r"(bar), "r"(ph) : "memory");
  return ok;
}
__device__ __forceinline__ void mbar_wait(uint32_t bar, uint32_t ph) {
  if (mbar_try(bar, ph)) return;
#pragma unroll 1
  for (int i = 0; i < 4000000; i++) if (mbar_try(bar, ph)) return;
  __trap();
}
__device__ __forceinline__ void tma2d(uint32_t dst, const CUtensorMap* tm, int c0, int c1, uint32_t bar) {
  asm volatile("cp.async.bulk.tensor.2d.shared::cluster.global.mbarrier::complete_tx::bytes [%0], [%1, {%3, %4}], [%2];" ::"r"(dst), "l"(tm), "r"(bar), "r"(c0), "r"(c1) : "memory");
}
__device__ __forceinline__ void bulk_ld(uint32_t dst, const void* src, uint32_t bytes, uint32_t bar) {
  asm volatile("cp.async.bulk.shared::cluster.global.mbarrier::complete_tx::bytes [%0], [%1], %2, [%3];" ::"r"(dst), "l"(src), "r"(bytes), "r"(bar) : "memory");
}
__device__ __forceinline__ unsigned ld_acq(const unsigned* p) {
  unsigned v;
  asm volatile("ld.acquire.gpu.global.u32 %0, [%1];" : "=r"(v) : "l"(p) : "memory");
  return v;
}
__device__ __forceinline__ void flag_wait(const unsigned* p, unsigned target) {
#pragma unroll 1
  for (int i = 0; i < 4000000; i++) {
    if (ld_acq(p) >= target) return;
    __nanosleep(20);
  }
  __trap();
}
__device__ __forceinline__ void flag_add(unsigned* p) {
  asm volatile("fence.acq_rel.gpu;\nred.relaxed.gpu.global.add.u32 [%0], 1;" ::"l"(p) : "memory");
}
__device__ __forceinline__ void fence_async_all() { asm volatile("fence.proxy.async;" ::: "memory"); }
__device__ __forceinline__ uint32_t pack_bf16(float lo, float hi) {
  uint32_t r;
  asm("cvt.rn.bf16x2.f32 %0, %1, %2;" : "=r"(r) : "f"(hi), "f"(lo));
  return r;
}
__device__ __forceinline__ float ex2f(float x) { float y; asm("ex2.approx.ftz.f32 %0, %1;" : "=f"(y) : "f"(x)); return y; }
__device__ __forceinline__ float tanh_fast(float x) { float y; asm("tanh.approx.f32 %0, %1;" : "=f"(y) : "f"(x)); return y; }
__device__ __forceinline__ float bf_lo(uint32_t v) { return __uint_as_float(v << 16); }
__device__ __forceinline__ float bf_hi(uint32_t v) { return __uint_as_float(v & 0xFFFF0000u); }
__device__ __forceinline__ uint32_t movm(uint32_t a) {
  uint32_t d;
  asm volatile("movmatrix.sync.aligned.m8n8.trans.b16 %0, %1;" : "=r"(d) : "r"(a));
  return d;
}

__device__ __forceinline__ void wgmma_ss128_tn(float (&d)[64], uint64_t da, uint64_t db, int sd) {
  asm volatile("{\n.reg .pred p;\nsetp.ne.b32 p, %66, 0;\n"
    "wgmma.mma_async.sync.aligned.m64n128k16.f32.bf16.bf16 {%0, %1, %2, %3, %4, %5, %6, %7, %8, %9, %10, %11, %12, %13, %14, %15, %16, %17, %18, %19, %20, %21, %22, %23, %24, %25, %26, %27, %28, %29, %30, %31, %32, %33, %34, %35, %36, %37, %38, %39, %40, %41, %42, %43, %44, %45, %46, %47, %48, %49, %50, %51, %52, %53, %54, %55, %56, %57, %58, %59, %60, %61, %62, %63}, %64, %65, p, 1, 1, 1, 0;\n}\n"
    : "+f"(d[0]), "+f"(d[1]), "+f"(d[2]), "+f"(d[3]), "+f"(d[4]), "+f"(d[5]), "+f"(d[6]), "+f"(d[7]), "+f"(d[8]), "+f"(d[9]), "+f"(d[10]), "+f"(d[11]), "+f"(d[12]), "+f"(d[13]), "+f"(d[14]), "+f"(d[15]), "+f"(d[16]), "+f"(d[17]), "+f"(d[18]), "+f"(d[19]), "+f"(d[20]), "+f"(d[21]), "+f"(d[22]), "+f"(d[23]), "+f"(d[24]), "+f"(d[25]), "+f"(d[26]), "+f"(d[27]), "+f"(d[28]), "+f"(d[29]), "+f"(d[30]), "+f"(d[31]), "+f"(d[32]), "+f"(d[33]), "+f"(d[34]), "+f"(d[35]), "+f"(d[36]), "+f"(d[37]), "+f"(d[38]), "+f"(d[39]), "+f"(d[40]), "+f"(d[41]), "+f"(d[42]), "+f"(d[43]), "+f"(d[44]), "+f"(d[45]), "+f"(d[46]), "+f"(d[47]), "+f"(d[48]), "+f"(d[49]), "+f"(d[50]), "+f"(d[51]), "+f"(d[52]), "+f"(d[53]), "+f"(d[54]), "+f"(d[55]), "+f"(d[56]), "+f"(d[57]), "+f"(d[58]), "+f"(d[59]), "+f"(d[60]), "+f"(d[61]), "+f"(d[62]), "+f"(d[63])
    : "l"(da), "l"(db), "r"(sd));
}
__device__ __forceinline__ void wgmma_ss128_tt(float (&d)[64], uint64_t da, uint64_t db, int sd) {
  asm volatile("{\n.reg .pred p;\nsetp.ne.b32 p, %66, 0;\n"
    "wgmma.mma_async.sync.aligned.m64n128k16.f32.bf16.bf16 {%0, %1, %2, %3, %4, %5, %6, %7, %8, %9, %10, %11, %12, %13, %14, %15, %16, %17, %18, %19, %20, %21, %22, %23, %24, %25, %26, %27, %28, %29, %30, %31, %32, %33, %34, %35, %36, %37, %38, %39, %40, %41, %42, %43, %44, %45, %46, %47, %48, %49, %50, %51, %52, %53, %54, %55, %56, %57, %58, %59, %60, %61, %62, %63}, %64, %65, p, 1, 1, 1, 1;\n}\n"
    : "+f"(d[0]), "+f"(d[1]), "+f"(d[2]), "+f"(d[3]), "+f"(d[4]), "+f"(d[5]), "+f"(d[6]), "+f"(d[7]), "+f"(d[8]), "+f"(d[9]), "+f"(d[10]), "+f"(d[11]), "+f"(d[12]), "+f"(d[13]), "+f"(d[14]), "+f"(d[15]), "+f"(d[16]), "+f"(d[17]), "+f"(d[18]), "+f"(d[19]), "+f"(d[20]), "+f"(d[21]), "+f"(d[22]), "+f"(d[23]), "+f"(d[24]), "+f"(d[25]), "+f"(d[26]), "+f"(d[27]), "+f"(d[28]), "+f"(d[29]), "+f"(d[30]), "+f"(d[31]), "+f"(d[32]), "+f"(d[33]), "+f"(d[34]), "+f"(d[35]), "+f"(d[36]), "+f"(d[37]), "+f"(d[38]), "+f"(d[39]), "+f"(d[40]), "+f"(d[41]), "+f"(d[42]), "+f"(d[43]), "+f"(d[44]), "+f"(d[45]), "+f"(d[46]), "+f"(d[47]), "+f"(d[48]), "+f"(d[49]), "+f"(d[50]), "+f"(d[51]), "+f"(d[52]), "+f"(d[53]), "+f"(d[54]), "+f"(d[55]), "+f"(d[56]), "+f"(d[57]), "+f"(d[58]), "+f"(d[59]), "+f"(d[60]), "+f"(d[61]), "+f"(d[62]), "+f"(d[63])
    : "l"(da), "l"(db), "r"(sd));
}
__device__ __forceinline__ void wgmma_ss72_nt(float (&d)[36], uint64_t da, uint64_t db, int sd) {
  asm volatile("{\n.reg .pred p;\nsetp.ne.b32 p, %38, 0;\n"
    "wgmma.mma_async.sync.aligned.m64n72k16.f32.bf16.bf16 {%0, %1, %2, %3, %4, %5, %6, %7, %8, %9, %10, %11, %12, %13, %14, %15, %16, %17, %18, %19, %20, %21, %22, %23, %24, %25, %26, %27, %28, %29, %30, %31, %32, %33, %34, %35}, %36, %37, p, 1, 1, 0, 1;\n}\n"
    : "+f"(d[0]), "+f"(d[1]), "+f"(d[2]), "+f"(d[3]), "+f"(d[4]), "+f"(d[5]), "+f"(d[6]), "+f"(d[7]), "+f"(d[8]), "+f"(d[9]), "+f"(d[10]), "+f"(d[11]), "+f"(d[12]), "+f"(d[13]), "+f"(d[14]), "+f"(d[15]), "+f"(d[16]), "+f"(d[17]), "+f"(d[18]), "+f"(d[19]), "+f"(d[20]), "+f"(d[21]), "+f"(d[22]), "+f"(d[23]), "+f"(d[24]), "+f"(d[25]), "+f"(d[26]), "+f"(d[27]), "+f"(d[28]), "+f"(d[29]), "+f"(d[30]), "+f"(d[31]), "+f"(d[32]), "+f"(d[33]), "+f"(d[34]), "+f"(d[35])
    : "l"(da), "l"(db), "r"(sd));
}
__device__ __forceinline__ void wgmma_rs64_t_z(float (&d)[32], uint32_t a0, uint32_t a1, uint32_t a2, uint32_t a3, uint64_t db) {
  asm volatile("{\n.reg .pred p;\nsetp.ne.b32 p, 0, 0;\n"
    "wgmma.mma_async.sync.aligned.m64n64k16.f32.bf16.bf16 {%0, %1, %2, %3, %4, %5, %6, %7, %8, %9, %10, %11, %12, %13, %14, %15, %16, %17, %18, %19, %20, %21, %22, %23, %24, %25, %26, %27, %28, %29, %30, %31}, {%32, %33, %34, %35}, %36, p, 1, 1, 1;\n}\n"
    : "=f"(d[0]), "=f"(d[1]), "=f"(d[2]), "=f"(d[3]), "=f"(d[4]), "=f"(d[5]), "=f"(d[6]), "=f"(d[7]), "=f"(d[8]), "=f"(d[9]), "=f"(d[10]), "=f"(d[11]), "=f"(d[12]), "=f"(d[13]), "=f"(d[14]), "=f"(d[15]), "=f"(d[16]), "=f"(d[17]), "=f"(d[18]), "=f"(d[19]), "=f"(d[20]), "=f"(d[21]), "=f"(d[22]), "=f"(d[23]), "=f"(d[24]), "=f"(d[25]), "=f"(d[26]), "=f"(d[27]), "=f"(d[28]), "=f"(d[29]), "=f"(d[30]), "=f"(d[31])
    : "r"(a0), "r"(a1), "r"(a2), "r"(a3), "l"(db));
}
__device__ __forceinline__ void wgmma_rs64_t(float (&d)[32], uint32_t a0, uint32_t a1, uint32_t a2, uint32_t a3, uint64_t db) {
  asm volatile("{\n.reg .pred p;\nsetp.ne.b32 p, 1, 0;\n"
    "wgmma.mma_async.sync.aligned.m64n64k16.f32.bf16.bf16 {%0, %1, %2, %3, %4, %5, %6, %7, %8, %9, %10, %11, %12, %13, %14, %15, %16, %17, %18, %19, %20, %21, %22, %23, %24, %25, %26, %27, %28, %29, %30, %31}, {%32, %33, %34, %35}, %36, p, 1, 1, 1;\n}\n"
    : "+f"(d[0]), "+f"(d[1]), "+f"(d[2]), "+f"(d[3]), "+f"(d[4]), "+f"(d[5]), "+f"(d[6]), "+f"(d[7]), "+f"(d[8]), "+f"(d[9]), "+f"(d[10]), "+f"(d[11]), "+f"(d[12]), "+f"(d[13]), "+f"(d[14]), "+f"(d[15]), "+f"(d[16]), "+f"(d[17]), "+f"(d[18]), "+f"(d[19]), "+f"(d[20]), "+f"(d[21]), "+f"(d[22]), "+f"(d[23]), "+f"(d[24]), "+f"(d[25]), "+f"(d[26]), "+f"(d[27]), "+f"(d[28]), "+f"(d[29]), "+f"(d[30]), "+f"(d[31])
    : "r"(a0), "r"(a1), "r"(a2), "r"(a3), "l"(db));
}
__device__ __forceinline__ void wgmma_rs24_n(float (&d)[12], uint32_t a0, uint32_t a1, uint32_t a2, uint32_t a3, uint64_t db) {
  asm volatile("{\n.reg .pred p;\nsetp.ne.b32 p, 1, 0;\n"
    "wgmma.mma_async.sync.aligned.m64n24k16.f32.bf16.bf16 {%0, %1, %2, %3, %4, %5, %6, %7, %8, %9, %10, %11}, {%12, %13, %14, %15}, %16, p, 1, 1, 0;\n}\n"
    : "+f"(d[0]), "+f"(d[1]), "+f"(d[2]), "+f"(d[3]), "+f"(d[4]), "+f"(d[5]), "+f"(d[6]), "+f"(d[7]), "+f"(d[8]), "+f"(d[9]), "+f"(d[10]), "+f"(d[11])
    : "r"(a0), "r"(a1), "r"(a2), "r"(a3), "l"(db));
}


constexpr int NW = 5, NKV = 4;
constexpr int SM_RES = 0;
constexpr int SM_W = 147456;
constexpr int SM_KV = SM_W + NW * 8192;
constexpr int SM_S2 = SM_KV + NKV * KVB;
constexpr int SM_BAR = SM_S2 + 1024;
constexpr int SM_TOTAL = SM_BAR + 512;
enum { B_RESF = 0, B_RESE = 9, B_WF = 18, B_WE = B_WF + NW, B_KVF = B_WE + NW, B_KVE = B_KVF + NKV, B_EPI = B_KVE + NKV, B_QRDY = B_EPI + 13, B_COUNT = B_QRDY + 4 };
static_assert(B_COUNT * 8 <= 512, "barriers");
static_assert(SM_TOTAL <= 232448, "smem");

constexpr uint32_t POLY_MASK = 0xB5;
constexpr uint32_t MAGIC1 = 0x43DF, MAGIC2 = 0xBF15, MAGIC3 = 0xB9AF;

__device__ __forceinline__ int qkv_chunk(int p) {
  return (p % 3) * 9 + p / 3;
}

struct Epi { int type; uint8_t* p0; uint8_t* p1; float b0, b1; uint32_t s2; };

__device__ __forceinline__ float gelu_half(float w) {
  float p = fmaf(w * w, 8.0f * 0.044715f * 0.7978845608028654f, 2.0f * 0.7978845608028654f);
  float t = tanh_fast(w * p);
  return fmaf(w, t, w);
}

template <int PHASE>
__device__ __forceinline__ void epi_slice(const float (&a)[64], const Epi& e, int sl) {
  if (e.type == 2) {
#pragma unroll
    for (int j = 0; j < 2; j++) {
      const int i = 2 * sl + j;
      uint32_t v0 = pack_bf16(gelu_half(fmaf(a[4 * i + 0], 0.5f, e.b0)), gelu_half(fmaf(a[4 * i + 1], 0.5f, e.b0)));
      uint32_t v1 = pack_bf16(gelu_half(fmaf(a[4 * i + 2], 0.5f, e.b1)), gelu_half(fmaf(a[4 * i + 3], 0.5f, e.b1)));
      *(uint32_t*)(e.p0 + i * 128) = v0;
      *(uint32_t*)(e.p1 + i * 128) = v1;
    }
  } else if (PHASE == 0 && e.type == 1) {
#pragma unroll
    for (int j = 0; j < 2; j++) {
      const int i = 2 * sl + j;
      float sx, sy;
      asm volatile("ld.shared.v2.f32 {%0,%1}, [%2];" : "=f"(sx), "=f"(sy) : "r"(e.s2 + i * 32));
      *(uint32_t*)(e.p0 + i * 128) = pack_bf16(a[4 * i + 0] * sx, a[4 * i + 1] * sy);
      *(uint32_t*)(e.p1 + i * 128) = pack_bf16(a[4 * i + 2] * sx, a[4 * i + 3] * sy);
    }
  } else if (PHASE == 1 && e.type == 3) {
#pragma unroll
    for (int j = 0; j < 2; j++) {
      const int i = 2 * sl + j;
      asm volatile("red.global.add.v4.f32 [%0], {%1,%2,%3,%4};" ::"l"(e.p0 + i * 512), "f"(a[4 * i]), "f"(a[4 * i + 1]), "f"(a[4 * i + 2]), "f"(a[4 * i + 3]) : "memory");
    }
  }
}

struct GState { uint32_t sb; int ws; uint32_t wph; int lane; };

template <int PHASE, bool DRAINED>
__device__ __forceinline__ void gemm_chunk(float (&cur)[64], float (&prev)[64], const Epi& e, GState& st, bool wait_res, bool free_res, int epi_bar, bool smem_epi) {
  const uint32_t bar = st.sb + SM_BAR;
  int pslot = (st.ws == 0) ? NW - 1 : st.ws - 1;
#pragma unroll
  for (int kb = 0; kb < 9; kb++) {
    if (kb == 8 && PHASE == 1 && smem_epi) {
      asm volatile("fence.proxy.async.shared::cta;" ::: "memory");
      asm volatile("bar.sync 3, 128;" ::: "memory");
    } else if (wait_res) mbar_wait(bar + (B_RESF + kb) * 8, PHASE);
    mbar_wait(bar + (B_WF + st.ws) * 8, st.wph);
    const uint32_t alo = ((st.sb + SM_W + st.ws * 8192) >> 4);
    const uint32_t blo = ((st.sb + SM_RES + kb * 16384) >> 4);
    wg_fence();
#pragma unroll
    for (int u = 0; u < 4; u++) {
      if (PHASE == 0) wgmma_ss128_tn(cur, mkdesc(alo + u * 128, desc_hi(1024, 1)), mkdesc(blo + u * 2, desc_hi(1024, 1)), (kb | u) != 0);
      else wgmma_ss128_tt(cur, mkdesc(alo + u * 128, desc_hi(1024, 1)), mkdesc((blo + u * 256) | desc_lbo(2048), desc_hi(128, 0)), (kb | u) != 0);
    }
    wg_commit();
    if (DRAINED) {
      if (kb < 8) epi_slice<PHASE>(prev, e, kb);
      if (kb > 0) wg_wait<1>();
    } else {
      if (kb > 0) epi_slice<PHASE>(prev, e, kb - 1);
      wg_wait<1>();
      if (kb == 0) pin(prev);
    }
    if (kb == (DRAINED ? 7 : 8) && epi_bar >= 0) { __syncwarp(); if (st.lane == 0) mbar_arrive(bar + epi_bar * 8); }
    if (st.lane == 0) {
      if (!(DRAINED && kb == 0)) mbar_arrive(bar + (B_WE + pslot) * 8);
      if (kb > 0 && free_res) mbar_arrive(bar + (B_RESE + kb - 1) * 8);
    }
    pslot = st.ws;
    if (++st.ws == NW) { st.ws = 0; st.wph ^= 1; }
  }
}
__device__ __forceinline__ void gemm_drain(float (&cur)[64], GState& st) {
  wg_wait<0>();
  pin(cur);
  int pslot = (st.ws == 0) ? NW - 1 : st.ws - 1;
  if (st.lane == 0) mbar_arrive(st.sb + SM_BAR + (B_WE + pslot) * 8);
}

__device__ __forceinline__ uint32_t exp2_pair_fix(float t0, float t1) {
  uint32_t z = __byte_perm(__float_as_uint(t0), __float_as_uint(t1), 0x6521);
  uint32_t mh;
  asm("lop3.b32 %0, %1, 0x007F007F, 0x9F809F80, 0xEA;" : "=r"(mh) : "r"(z));
  uint32_t e = z - mh;
  uint32_t r;
  asm("fma.rn.bf16x2 %0, %1, %2, %3;" : "=r"(r) : "r"(z), "r"(mh), "r"(e));
  return r;
}
__device__ __forceinline__ void softmax_tile(const float (&s)[32], uint32_t (&p)[16]) {
#pragma unroll
  for (int i = 0; i < 8; i++) {
    if ((POLY_MASK >> i) & 1) {
      p[2 * i + 0] = exp2_pair_fix(s[4 * i + 0], s[4 * i + 1]);
      p[2 * i + 1] = exp2_pair_fix(s[4 * i + 2], s[4 * i + 3]);
    } else {
      p[2 * i + 0] = pack_bf16(ex2f(s[4 * i + 0]), ex2f(s[4 * i + 1]));
      p[2 * i + 1] = pack_bf16(ex2f(s[4 * i + 2]), ex2f(s[4 * i + 3]));
    }
  }
}

__global__ void __launch_bounds__(512, 1)
main_kernel(const __grid_constant__ CUtensorMap tm_y, const __grid_constant__ CUtensorMap tm_wqkv,
            const __grid_constant__ CUtensorMap tm_w1, const __grid_constant__ CUtensorMap tm_w2,
            const bf16* __restrict__ x, const bf16* __restrict__ b1) {
  extern __shared__ __align__(1024) uint8_t smem[];
  const uint32_t sb = smem_u32(smem);
  const uint32_t bar = sb + SM_BAR;
  const int tid = threadIdx.x, warp = tid >> 5, lane = tid & 31;
  const int r = blockIdx.x >> 3, g = blockIdx.x & 7;
  const int nq = (g < 3) ? 4 : 3;
  const int nA = nq + 9;

  {
    const int row = r * 128 + g * 16 + warp;
    const uint32_t* xr = (const uint32_t*)(x + (size_t)row * D_);
    uint32_t xv[9];
#pragma unroll
    for (int j = 0; j < 9; j++) xv[j] = __ldg(xr + j * 32 + lane);
    if (tid == 0) {
      for (int i = 0; i < B_COUNT; i++) {
        int cnt = 1;
        if ((i >= B_RESE && i < B_WF) || (i >= B_WE && i < B_KVF) || (i >= B_EPI && i < B_QRDY)) cnt = 4;
        if (i >= B_KVE && i < B_EPI) cnt = 8;
        mbar_init(bar + i * 8, cnt);
      }
      asm volatile("fence.mbarrier_init.release.cluster;" ::: "memory");
    }
    if (tid < 256) {
      const int j = tid >> 6, grp = (tid >> 2) & 15, rw = tid & 3;
      const bool poly = (POLY_MASK >> (grp & 7)) & 1;
      uint32_t v = (rw == 1) ? 0x3F80u : (!poly ? 0u : (rw == 0 ? MAGIC1 : (rw == 2 ? MAGIC2 : MAGIC3)));
      v |= v << 16;
      *(uint4*)(g_kv + (size_t)((g + 8 * j) * NRT + r) * KVB + 4 * 2048 + grp * 128 + 64 + rw * 16) = make_uint4(v, v, v, v);
    }
    float sum = 0.f;
#pragma unroll
    for (int j = 0; j < 9; j++) sum += bf_lo(xv[j]) + bf_hi(xv[j]);
#pragma unroll
    for (int o = 16; o; o >>= 1) sum += __shfl_xor_sync(~0u, sum, o);
    const float mu = sum * (1.0f / D_);
    float sq = 0.f;
#pragma unroll
    for (int j = 0; j < 9; j++) { float a = bf_lo(xv[j]) - mu, b = bf_hi(xv[j]) - mu; sq += a * a + b * b; }
#pragma unroll
    for (int o = 16; o; o >>= 1) sq += __shfl_xor_sync(~0u, sq, o);
    const float var = sq * (1.0f / D_);
    const float rs1 = rsqrtf(var + 1e-5f);
    const float s2 = sqrtf(var * rs1 * rs1 + 1e-5f);
    const float sc = rs1 / s2;
    uint32_t* yr = (uint32_t*)(g_y + (size_t)row * D_);
#pragma unroll
    for (int j = 0; j < 9; j++) yr[j * 32 + lane] = pack_bf16((bf_lo(xv[j]) - mu) * sc, (bf_hi(xv[j]) - mu) * sc);
    if (lane == 0) { g_s2[row] = s2; g_s2[S_ + row] = s2 * (0.23570226039551584f * 1.4426950408889634f); }
  }
  __syncthreads();

  if (warp >= 12) {
    asm volatile("setmaxnreg.dec.sync.aligned.u32 32;");
    if (lane == 0) {
      if (warp == 12) {
        int s = 0; uint32_t ph = 1;
        for (int ch = 0; ch < nA + 9; ch++) {
          const CUtensorMap* tm; int c0, k0;
          if (ch < nq) { tm = &tm_wqkv; c0 = qkv_chunk(g + 8 * ch) * 64; k0 = 0; }
          else if (ch < nA) { tm = &tm_w1; c0 = g * 576 + (ch - nq) * 64; k0 = 0; }
          else { int c = ch - nA + g; if (c >= 9) c -= 9; tm = &tm_w2; c0 = c * 64; k0 = g * 576; }
#pragma unroll 1
          for (int kb = 0; kb < 9; kb++) {
            mbar_wait(bar + (B_WE + s) * 8, ph);
            mbar_expect(bar + (B_WF + s) * 8, 8192);
            tma2d(sb + SM_W + s * 8192, tm, c0, k0 + kb * 64, bar + (B_WF + s) * 8);
            if (++s == NW) { s = 0; ph ^= 1; }
          }
        }
      } else if (warp == 13) {
        int s = 0; uint32_t ph = 1;
        for (int j = 0; j < 4; j++) {
          const int h = g + 8 * j;
          const int c_lo = (h * 18) >> 6, c_hi = (h * 18 + 17) >> 6;
          for (int part = 0; part < 3; part++) {
            flag_wait(&g_flags.qkv[part * 9 + c_lo], NRT);
            flag_wait(&g_flags.qkv[part * 9 + c_hi], NRT);
          }
          fence_async_all();
          mbar_arrive(bar + (B_QRDY + j) * 8);
          const uint8_t* src = g_kv + (size_t)h * NRT * KVB;
#pragma unroll 1
          for (int t = 0; t < NRT; t++) {
            mbar_wait(bar + (B_KVE + s) * 8, ph);
            mbar_expect(bar + (B_KVF + s) * 8, KVB);
            bulk_ld(sb + SM_KV + s * KVB, src + (size_t)t * KVB, KVB, bar + (B_KVF + s) * 8);
            if (++s == NKV) { s = 0; ph ^= 1; }
          }
        }
      } else if (warp == 14) {
        flag_add(&g_flags.ln[r]);
        flag_wait(&g_flags.ln[r], NG);
        fence_async_all();
        for (int kb = 0; kb < 9; kb++) {
          mbar_expect(bar + (B_RESF + kb) * 8, 16384 + (kb == 0 ? 1024 : 0));
          tma2d(sb + SM_RES + kb * 16384, &tm_y, kb * 64, r * 128, bar + (B_RESF + kb) * 8);
          if (kb == 0) {
            bulk_ld(sb + SM_S2, g_s2 + r * 128, 512, bar + B_RESF * 8);
            bulk_ld(sb + SM_S2 + 512, g_s2 + S_ + r * 128, 512, bar + B_RESF * 8);
          }
        }
        flag_wait(&g_flags.zero[r], NG);
        const uint8_t* src = g_h + (size_t)(r * 72 + g * 9) * 16384;
        for (int kb = 0; kb < 8; kb++) {
          mbar_wait(bar + (B_EPI + nq + kb) * 8, 0);
          mbar_wait(bar + (B_RESE + kb) * 8, 0);
          if (kb == 0 || kb == 7) { asm volatile("fence.acq_rel.gpu;" ::: "memory"); fence_async_all(); }
          mbar_expect(bar + (B_RESF + kb) * 8, 16384);
          bulk_ld(sb + SM_RES + kb * 16384, src + (size_t)kb * 16384, 16384, bar + (B_RESF + kb) * 8);
        }
      } else {
        for (int ch = 0; ch < nq; ch++) {
          mbar_wait(bar + (B_EPI + ch) * 8, 0);
          flag_add(&g_flags.qkv[qkv_chunk(g + 8 * ch)]);
        }
      }
    }
  } else if (warp >= 8) {
    asm volatile("setmaxnreg.inc.sync.aligned.u32 176;");
    const int w = warp - 8, gq = lane >> 2, t = lane & 3;
    GState st{sb, 0, 0u, lane};
    float d0[64], d1[64];
#pragma unroll
    for (int i = 0; i < 64; i++) { d0[i] = 0.f; d1[i] = 0.f; }
    pin(d0); pin(d1);
    auto make_epi = [&](int ch) {
      Epi e; e.type = 0; e.p0 = e.p1 = nullptr; e.b0 = e.b1 = 0.f; e.s2 = 0;
      if (ch < 0) return e;
      if (ch < nq) {
        const int cq = qkv_chunk(g + 8 * ch);
        const int part = cq / 9;
        e.type = 1;
        e.s2 = sb + SM_S2 + (part == 0 ? 512 : 0) + t * 8;
        uint8_t* pp[2];
#pragma unroll
        for (int hf = 0; hf < 2; hf++) {
          const int jj = (cq - part * 9) * 64 + w * 16 + hf * 8 + gq;
          const int head = jj / 18, dim = jj - head * 18;
          uint8_t* base; int off;
          if (part == 0) { base = g_q + (size_t)(head * NRT + r) * QB; off = (dim >> 3) * 2048 + (dim & 7) * 16; }
          else {
            base = g_kv + (size_t)(head * NRT + r) * KVB;
            off = (dim < 16) ? ((part - 1) * 2 + (dim >> 3)) * 2048 + (dim & 7) * 16 : 4 * 2048 + ((part - 1) * 2 + dim - 16) * 16;
          }
          pp[hf] = base + off + t * 4;
        }
        e.p0 = pp[0]; e.p1 = pp[1];
      } else {
        const int c = ch - nq;
        e.type = 2;
        const int f = g * 576 + c * 64 + w * 16 + gq;
        e.b0 = 0.5f * __bfloat162float(b1[f]);
        e.b1 = 0.5f * __bfloat162float(b1[f + 8]);
        uint8_t* base = (c == 8) ? (smem + SM_RES + 8 * 16384) : (g_h + (size_t)(r * 72 + g * 9 + c) * 16384);
        e.p0 = base + (2 * w) * 2048 + lane * 4;
        e.p1 = e.p0 + 2048;
      }
      return e;
    };
    int ch = -(nA & 1);
#pragma unroll 1
    for (; ch < nA; ch += 2) {
      if (ch >= 0) {
        Epi e = make_epi(ch - 1);
        gemm_chunk<0, true>(d0, d1, e, st, ch == 0, false, ch > 0 ? B_EPI + ch - 1 : -1, false);
        Epi e2 = make_epi(ch);
        gemm_chunk<0, false>(d1, d0, e2, st, false, ch + 2 == nA, B_EPI + ch, false);
      } else {
        Epi e = make_epi(-1);
        gemm_chunk<0, true>(d1, d0, e, st, true, false, -1, false);
      }
      gemm_drain(d1, st);
    }
    asm volatile("bar.sync 3, 128;" ::: "memory");
    auto make_red = [&](int c2) {
      Epi e; e.type = 3; e.b0 = e.b1 = 0.f; e.s2 = 0; e.p1 = nullptr;
      int c = c2 + g; if (c >= 9) c -= 9;
      e.p0 = (uint8_t*)(g_acc + (size_t)(r * 9 + c) * 8192 + w * 2048 + lane * 4);
      return e;
    };
#pragma unroll 1
    for (int c2 = 0; c2 < 9; c2 += 2) {
      Epi e = (c2 == 0) ? make_epi(nA - 1) : make_red(c2 - 1);
      gemm_chunk<1, true>(d0, d1, e, st, c2 == 0, false, -1, c2 == 0);
      Epi e2 = make_red(c2);
      if (c2 < 8) {
        gemm_chunk<1, false>(d1, d0, e2, st, false, false, -1, false);
        gemm_drain(d1, st);
      } else {
        gemm_drain(d0, st);
#pragma unroll
        for (int sl = 0; sl < 8; sl++) epi_slice<1>(d0, e2, sl);
      }
    }
  } else {
    asm volatile("setmaxnreg.inc.sync.aligned.u32 152;");
    const int gq = lane >> 2, t = lane & 3;
    {
      float4* z = (float4*)(g_acc + (size_t)r * 9 * 8192 + g * 9216);
#pragma unroll
      for (int i = 0; i < 9; i++) z[i * 256 + tid] = make_float4(0.f, 0.f, 0.f, 0.f);
      asm volatile("bar.sync 1, 256;" ::: "memory");
      if (tid == 0) flag_add(&g_flags.zero[r]);
    }
    int slot = 0; uint32_t ph = 0;
    constexpr uint32_t KHI = desc_hi(128, 0), VHI = desc_hi(2048, 0);
#pragma unroll 1
    for (int j = 0; j < 4; j++) {
      const int h = g + 8 * j;
      mbar_wait(bar + (B_QRDY + j) * 8, 0);
      uint32_t q0, q1, q2, q3, q4, q5;
      {
        const uint8_t* qp = g_q + (size_t)(h * NRT + r) * QB + (warp * 2) * 128 + lane * 4;
        q0 = __ldcg((const uint32_t*)(qp));
        q1 = __ldcg((const uint32_t*)(qp + 128));
        q2 = __ldcg((const uint32_t*)(qp + 2048));
        q3 = __ldcg((const uint32_t*)(qp + 2048 + 128));
        q4 = (lane < 8) ? __ldcg((const uint32_t*)(qp + 4096)) : 0u;
        q5 = (lane < 8) ? __ldcg((const uint32_t*)(qp + 4096 + 128)) : 0u;
        q0 = movm(q0); q1 = movm(q1); q2 = movm(q2); q3 = movm(q3); q4 = movm(q4); q5 = movm(q5);
        if (t == 2) { q4 = 0x00003F80u; q5 = 0x00003F80u; }
        if (t == 3) { q4 = 0x3F803F80u; q5 = 0x3F803F80u; }
      }
      float o[12], sa[32], sbb[32];
      uint32_t pa[16], pb[16];
#pragma unroll
      for (int i = 0; i < 12; i++) o[i] = 0.f;
      pin(o);
      uint32_t cur = (sb + SM_KV + slot * KVB) >> 4;
      mbar_wait(bar + (B_KVF + slot) * 8, ph);
      wg_fence();
      wgmma_rs64_t_z(sa, q0, q1, q2, q3, mkdesc(cur | desc_lbo(2048), KHI));
      wgmma_rs64_t(sa, q4, q5, 0u, 0u, mkdesc(cur + 512, KHI));
      wg_commit();
      wg_wait<0>();
      int pslot = -1;
#pragma unroll 1
      for (int s = 0; s < NRT; s++) {
        pin(sa);
        wg_fence();
        wgmma_rs64_t_z(sbb, q0, q1, q2, q3, mkdesc((cur + 64) | desc_lbo(2048), KHI));
        wgmma_rs64_t(sbb, q4, q5, 0u, 0u, mkdesc(cur + 512 + 64, KHI));
        wg_commit();
        softmax_tile(sa, pa);
        pin(pa);
        wg_fence();
#pragma unroll
        for (int k = 0; k < 4; k++) wgmma_rs24_n(o, pa[4 * k], pa[4 * k + 1], pa[4 * k + 2], pa[4 * k + 3], mkdesc((cur + 256 + k * 16) | desc_lbo(128), VHI));
        wg_commit();
        wg_wait<1>();
        pin(sbb);
        if (pslot >= 0 && lane == 0) mbar_arrive(bar + (B_KVE + pslot) * 8);
        pslot = slot;
        if (++slot == NKV) { slot = 0; ph ^= 1; }
        uint32_t nxt = cur;
        if (s + 1 < NRT) { nxt = (sb + SM_KV + slot * KVB) >> 4; mbar_wait(bar + (B_KVF + slot) * 8, ph); }
        wg_fence();
        wgmma_rs64_t_z(sa, q0, q1, q2, q3, mkdesc(nxt | desc_lbo(2048), KHI));
        wgmma_rs64_t(sa, q4, q5, 0u, 0u, mkdesc(nxt + 512, KHI));
        wg_commit();
        softmax_tile(sbb, pb);
        pin(pb);
        wg_fence();
#pragma unroll
        for (int k = 0; k < 4; k++) wgmma_rs24_n(o, pb[4 * k], pb[4 * k + 1], pb[4 * k + 2], pb[4 * k + 3], mkdesc((cur + 256 + 64 + k * 16) | desc_lbo(128), VHI));
        wg_commit();
        wg_wait<1>();
        cur = nxt;
      }
      wg_wait<0>();
      pin(o);
      if (lane == 0) mbar_arrive(bar + (B_KVE + pslot) * 8);
      const float l0 = __shfl_sync(~0u, o[9], (lane & ~3) + 2), l1 = __shfl_sync(~0u, o[11], (lane & ~3) + 2);
      const float i0 = 1.0f / l0, i1 = 1.0f / l1;
      uint32_t* op = (uint32_t*)(g_o + (size_t)(r * 128 + warp * 16 + gq) * D_ + h * 18) + t;
      op[0] = pack_bf16(o[0] * i0, o[1] * i0);
      op[4] = pack_bf16(o[4] * i0, o[5] * i0);
      op[8 * 288] = pack_bf16(o[2] * i1, o[3] * i1);
      op[8 * 288 + 4] = pack_bf16(o[6] * i1, o[7] * i1);
      if (t == 1) {
        op[7] = pack_bf16(o[8] * i0, o[9] * i0);
        op[8 * 288 + 7] = pack_bf16(o[10] * i1, o[11] * i1);
      }
    }
  }
}

constexpr int TS_A = 0, TS_B = 147456, TS_BAR = TS_B + 82944, TS_TOTAL = TS_BAR + 128;
__global__ void __launch_bounds__(256, 1)
tail_kernel(const __grid_constant__ CUtensorMap tm_o, const bf16* __restrict__ x, const bf16* __restrict__ wo,
            const bf16* __restrict__ b2, bf16* __restrict__ out) {
  extern __shared__ __align__(1024) uint8_t smem[];
  const uint32_t sb = smem_u32(smem);
  const int tid = threadIdx.x, warp = tid >> 5, lane = tid & 31;
  const int r = blockIdx.x >> 3, g = blockIdx.x & 7;
  if (tid == 0) {
    for (int i = 0; i < 9; i++) mbar_init(sb + TS_BAR + i * 8, 1);
    asm volatile("fence.mbarrier_init.release.cluster;" ::: "memory");
    for (int kb = 0; kb < 9; kb++) {
      mbar_expect(sb + TS_BAR + kb * 8, 16384);
      tma2d(sb + TS_A + kb * 16384, &tm_o, kb * 64, r * 128, sb + TS_BAR + kb * 8);
    }
  }
  if (blockIdx.x == 0 && tid < (int)(sizeof(Flags) / 4)) ((unsigned*)&g_flags)[tid] = 0u;
  for (int i = tid; i < 9 * 576; i += 256) {
    const int k = i / 9, c = i - k * 9;
    uint4 v = __ldg((const uint4*)(wo + (size_t)k * D_ + g * 72 + c * 8));
    *(uint4*)(smem + TS_B + c * 9216 + k * 16) = v;
  }
  asm volatile("fence.proxy.async.shared::cta;" ::: "memory");
  __syncthreads();
  const int wg = warp >> 2;
  float d[36];
#pragma unroll
  for (int i = 0; i < 36; i++) d[i] = 0.f;
  pin(d);
#pragma unroll 1
  for (int kb = 0; kb < 9; kb++) {
    mbar_wait(sb + TS_BAR + kb * 8, 0);
    wg_fence();
#pragma unroll
    for (int u = 0; u < 4; u++)
      wgmma_ss72_nt(d, mkdesc(((sb + TS_A + kb * 16384 + wg * 8192) >> 4) + u * 2, desc_hi(1024, 1)),
                    mkdesc((((sb + TS_B) >> 4) + (kb * 64 + u * 16)) | desc_lbo(128), desc_hi(9216, 0)), 1);
    wg_commit();
  }
  wg_wait<0>();
  pin(d);
  const int gq = lane >> 2, t = lane & 3;
#pragma unroll
  for (int i = 0; i < 9; i++) {
#pragma unroll
    for (int hf = 0; hf < 2; hf++) {
      const int tok = warp * 16 + hf * 8 + gq;
      const int col = g * 72 + i * 8 + t * 2;
      float a[2];
#pragma unroll
      for (int c = 0; c < 2; c++) {
        const int cc = col + c;
        a[c] = __ldcg(g_acc + (size_t)(r * 9 + (cc >> 6)) * 8192 + ((cc & 63) >> 4) * 2048 + (tok >> 3) * 128 +
                      ((cc & 7) * 4 + ((tok & 7) >> 1)) * 4 + ((cc >> 3) & 1) * 2 + (tok & 1));
      }
      const size_t o = (size_t)(r * 128 + tok) * D_ + col;
      const uint32_t xv = __ldg((const uint32_t*)(x + o));
      const uint32_t bv = __ldg((const uint32_t*)(b2 + col));
      *(uint32_t*)(out + o) = pack_bf16(d[4 * i + 2 * hf] + a[0] + bf_lo(xv) + bf_lo(bv), d[4 * i + 2 * hf + 1] + a[1] + bf_hi(xv) + bf_hi(bv));
    }
  }
}

typedef CUresult (*enc_fn)(CUtensorMap*, CUtensorMapDataType, cuuint32_t, void*, const cuuint64_t*, const cuuint64_t*,
                           const cuuint32_t*, const cuuint32_t*, CUtensorMapInterleave, CUtensorMapSwizzle,
                           CUtensorMapL2promotion, CUtensorMapFloatOOBfill);
static void make_map(enc_fn enc, CUtensorMap* tm, const void* p, int cols, int rows, int bc, int br) {
  cuuint64_t gd[2] = {(cuuint64_t)cols, (cuuint64_t)rows};
  cuuint64_t gs[1] = {(cuuint64_t)cols * 2};
  cuuint32_t bx[2] = {(cuuint32_t)bc, (cuuint32_t)br};
  cuuint32_t es[2] = {1, 1};
  enc(tm, CU_TENSOR_MAP_DATA_TYPE_BFLOAT16, 2, (void*)p, gd, gs, bx, es, CU_TENSOR_MAP_INTERLEAVE_NONE,
      CU_TENSOR_MAP_SWIZZLE_128B, CU_TENSOR_MAP_L2_PROMOTION_L2_256B, CU_TENSOR_MAP_FLOAT_OOB_FILL_NONE);
}

extern "C" void kernel_launch(void* const* d_in, const int* in_sizes, int n_in, void* d_out, int out_size) {
  const bf16* x = (const bf16*)d_in[0];
  const bf16* wqkv = (const bf16*)d_in[1];
  const bf16* wo = (const bf16*)d_in[2];
  const bf16* w1 = (const bf16*)d_in[4];
  const bf16* b1 = (const bf16*)d_in[5];
  const bf16* w2 = (const bf16*)d_in[6];
  const bf16* b2 = (const bf16*)d_in[7];
  static enc_fn enc = nullptr;
  static void *py = nullptr, *po = nullptr;
  if (!enc) {
    void* fn = nullptr;
    cudaDriverEntryPointQueryResult qr;
    cudaGetDriverEntryPoint("cuTensorMapEncodeTiled", &fn, cudaEnableDefault, &qr);
    enc = (enc_fn)fn;
    cudaGetSymbolAddress(&py, g_y);
    cudaGetSymbolAddress(&po, g_o);
    cudaFuncSetAttribute(main_kernel, cudaFuncAttributeMaxDynamicSharedMemorySize, SM_TOTAL);
    cudaFuncSetAttribute(tail_kernel, cudaFuncAttributeMaxDynamicSharedMemorySize, TS_TOTAL);
  }
  CUtensorMap tm_y, tm_wqkv, tm_w1, tm_w2, tm_o;
  make_map(enc, &tm_y, py, D_, S_, 64, 128);
  make_map(enc, &tm_o, po, D_, S_, 64, 128);
  make_map(enc, &tm_wqkv, wqkv, 3 * D_, D_, 64, 64);
  make_map(enc, &tm_w1, w1, F_, D_, 64, 64);
  make_map(enc, &tm_w2, w2, D_, F_, 64, 64);
  main_kernel<<<NRT * NG, 512, SM_TOTAL>>>(tm_y, tm_wqkv, tm_w1, tm_w2, x, b1);
  tail_kernel<<<NRT * NG, 256, TS_TOTAL>>>(tm_o, x, wo, b2, (bf16*)d_out);
}
```

```cpp
#include <cuda_runtime.h>
#include <cuda_bf16.h>
#include <cuda.h>
#include <stdint.h>

typedef __nv_bfloat16 bf16;

constexpr int S_ = 2048, D_ = 576, F_ = 4608, H_ = 32, DH_ = 18;
constexpr int NRT = 16;
constexpr int NG = 8;

constexpr int KVB = 10240;
constexpr int QB = 6144;
__device__ __align__(1024) uint8_t g_q[H_ * NRT * QB];
__device__ __align__(1024) uint8_t g_kv[H_ * NRT * KVB];
__device__ __align__(1024) uint8_t g_h[NRT * 72 * 16384];
__device__ __align__(1024) float g_acc[NRT * 9 * 8192];
__device__ __align__(1024) bf16 g_o[S_ * D_];
struct Flags {
  unsigned zero[NRT];
  unsigned red[NRT];
  unsigned ocnt[NRT * 4];
  unsigned done;
  unsigned qkv[32];
  unsigned kmax[H_];
  unsigned kcnt[H_];
};
__device__ Flags g_flags;
#define TS(idx) do {} while (0)

__device__ __forceinline__ uint32_t smem_u32(const void* p) { return (uint32_t)__cvta_generic_to_shared(p); }
__device__ __forceinline__ void wg_fence() { asm volatile("wgmma.fence.sync.aligned;" ::: "memory"); }
__device__ __forceinline__ void wg_commit() { asm volatile("wgmma.commit_group.sync.aligned;" ::: "memory"); }
template <int N> __device__ __forceinline__ void wg_wait() { asm volatile("wgmma.wait_group.sync.aligned %0;" ::"n"(N) : "memory"); }
template <int N> __device__ __forceinline__ void pin(float (&d)[N]) {
#pragma unroll
  for (int i = 0; i < N; i++) asm volatile("" : "+f"(d[i])::"memory");
}
template <int N> __device__ __forceinline__ void pin(uint32_t (&d)[N]) {
#pragma unroll
  for (int i = 0; i < N; i++) asm volatile("" : "+r"(d[i])::"memory");
}
__device__ __forceinline__ uint64_t mkdesc(uint32_t lo, uint32_t hi) { return ((uint64_t)hi << 32) | lo; }
__host__ __device__ constexpr uint32_t desc_lbo(uint32_t lbo) { return (lbo >> 4) << 16; }
__host__ __device__ constexpr uint32_t desc_hi(uint32_t sbo, uint32_t swz) { return (sbo >> 4) | (swz << 30); }

__device__ __forceinline__ void mbar_init(uint32_t bar, int cnt) { asm volatile("mbarrier.init.shared::cta.b64 [%0], %1;" ::"r"(bar), "r"(cnt)); }
__device__ __forceinline__ void mbar_expect(uint32_t bar, uint32_t bytes) {
  asm volatile("mbarrier.arrive.expect_tx.shared::cta.b64 _, [%0], %1;" ::"r"(bar), "r"(bytes) : "memory");
}
__device__ __forceinline__ void mbar_arrive(uint32_t bar) { asm volatile("mbarrier.arrive.shared::cta.b64 _, [%0];" ::"r"(bar) : "memory"); }
__device__ __forceinline__ uint32_t mbar_test(uint32_t bar, uint32_t ph) {
  uint32_t ok;
  asm volatile("{\n.reg .pred p;\nmbarrier.test_wait.parity.shared::cta.b64 p, [%1], %2;\nselp.u32 %0,1,0,p;\n}" : "=r"(ok) : "r"(bar), "r"(ph) : "memory");
  return ok;
}
#define TRY_ "mbarrier.try_wait.parity.shared::cta.b64 p, [%0], %1;\n@p bra MW_DONE;\n"
__device__ __forceinline__ void mbar_wait(uint32_t bar, uint32_t ph) {
  asm volatile(
      "{\n.reg .pred p;\n.reg .u32 c;\n"
      "mov.u32 c, 0;\n"
      "MW_LOOP:\n" TRY_ TRY_
      "add.u32 c, c, 1;\n"
      "setp.lt.u32 p, c, 4000000;\n"
      "@p bra MW_LOOP;\n"
      "trap;\n"
      "MW_DONE:\n}" ::"r"(bar), "r"(ph) : "memory");
}
__device__ __forceinline__ void mbar_wait_unless(uint32_t ok, uint32_t bar, uint32_t ph) {
  asm volatile(
      "{\n.reg .pred p;\n.reg .u32 c;\n"
      "setp.ne.u32 p, %2, 0;\n"
      "@p bra MW_DONE;\n"
      "mov.u32 c, 0;\n"
      "MW_LOOP:\n" TRY_
      "add.u32 c, c, 1;\n"
      "setp.lt.u32 p, c, 4000000;\n"
      "@p bra MW_LOOP;\n"
      "trap;\n"
      "MW_DONE:\n}" ::"r"(bar), "r"(ph), "r"(ok) : "memory");
}
__device__ __forceinline__ void mbar_wait_slow(uint32_t bar, uint32_t ph) {
  asm volatile(
      "{\n.reg .pred p;\n.reg .u32 c;\n"
      "mov.u32 c, 0;\n"
      "MS_LOOP:\n"
      "mbarrier.try_wait.parity.shared::cta.b64 p, [%0], %1;\n"
      "@p bra MS_DONE;\n"
      "nanosleep.u32 64;\n"
      "add.u32 c, c, 1;\n"
      "setp.lt.u32 p, c, 1000000;\n"
      "@p bra MS_LOOP;\n"
      "trap;\n"
      "MS_DONE:\n}" ::"r"(bar), "r"(ph) : "memory");
}
__device__ __forceinline__ void mbar_wait_sleep(uint32_t bar, uint32_t ph) {
  asm volatile(
      "{\n.reg .pred p;\n.reg .u32 c;\n"
      "mov.u32 c, 0;\n"
      "MS_LOOP:\n"
      "mbarrier.try_wait.parity.shared::cta.b64 p, [%0], %1;\n"
      "@p bra MS_DONE;\n"
      "nanosleep.u32 250;\n"
      "add.u32 c, c, 1;\n"
      "setp.lt.u32 p, c, 1000000;\n"
      "@p bra MS_LOOP;\n"
      "trap;\n"
      "MS_DONE:\n}" ::"r"(bar), "r"(ph) : "memory");
}
__device__ __forceinline__ void nb_sync(int id, int n) { asm volatile("bar.sync %0, %1;" ::"r"(id), "r"(n) : "memory"); }
__device__ __forceinline__ void nb_arrive(int id, int n) { asm volatile("bar.arrive %0, %1;" ::"r"(id), "r"(n) : "memory"); }
__device__ __forceinline__ void stg32(void* p, uint32_t v) { asm volatile("st.global.b32 [%0], %1;" ::"l"(p), "r"(v) : "memory"); }
__device__ __forceinline__ void sts32(uint32_t a, uint32_t v) { asm volatile("st.shared.b32 [%0], %1;" ::"r"(a), "r"(v) : "memory"); }
__device__ __forceinline__ bool elect_one() {
  uint32_t p;
  asm volatile("{\n.reg .pred q;\nelect.sync _|q, 0xffffffff;\nselp.u32 %0, 1, 0, q;\n}" : "=r"(p));
  return p != 0;
}
__device__ __forceinline__ void tma2d(uint32_t dst, const CUtensorMap* tm, int c0, int c1, uint32_t bar) {
  asm volatile("cp.async.bulk.tensor.2d.shared::cluster.global.mbarrier::complete_tx::bytes [%0], [%1, {%3, %4}], [%2];" ::"r"(dst), "l"(tm), "r"(bar), "r"(c0), "r"(c1) : "memory");
}
__device__ __forceinline__ void bulk_ld(uint32_t dst, const void* src, uint32_t bytes, uint32_t bar) {
  asm volatile("cp.async.bulk.shared::cluster.global.mbarrier::complete_tx::bytes [%0], [%1], %2, [%3];" ::"r"(dst), "l"(src), "r"(bytes), "r"(bar) : "memory");
}
__device__ __forceinline__ void flag_wait(const unsigned* p, unsigned target) {
  asm volatile(
      "{\n.reg .pred p;\n.reg .u32 c, v;\n"
      "mov.u32 c, 0;\n"
      "FW_LOOP:\n"
      "ld.acquire.gpu.global.u32 v, [%0];\n"
      "setp.ge.u32 p, v, %1;\n"
      "@p bra FW_DONE;\n"
      "nanosleep.u32 40;\n"
      "add.u32 c, c, 1;\n"
      "setp.lt.u32 p, c, 4000000;\n"
      "@p bra FW_LOOP;\n"
      "trap;\n"
      "FW_DONE:\n}" ::"l"(p), "r"(target) : "memory");
}
__device__ __forceinline__ void flag_add(unsigned* p) {
  asm volatile("fence.acq_rel.gpu;\nred.relaxed.gpu.global.add.u32 [%0], 1;" ::"l"(p) : "memory");
}
__device__ __forceinline__ void fence_async_all() { asm volatile("fence.proxy.async;" ::: "memory"); }
__device__ __forceinline__ uint32_t pack_bf16(float lo, float hi) {
  uint32_t r;
  asm("cvt.rn.bf16x2.f32 %0, %1, %2;" : "=r"(r) : "f"(hi), "f"(lo));
  return r;
}
__device__ __forceinline__ float ex2f(float x) { float y; asm("ex2.approx.ftz.f32 %0, %1;" : "=f"(y) : "f"(x)); return y; }
__device__ __forceinline__ float tanh_fast(float x) { float y; asm("tanh.approx.f32 %0, %1;" : "=f"(y) : "f"(x)); return y; }
__device__ __forceinline__ float bf_lo(uint32_t v) { return __uint_as_float(v << 16); }
__device__ __forceinline__ float bf_hi(uint32_t v) { return __uint_as_float(v & 0xFFFF0000u); }
__device__ __forceinline__ uint32_t movm(uint32_t a) {
  uint32_t d;
  asm volatile("movmatrix.sync.aligned.m8n8.trans.b16 %0, %1;" : "=r"(d) : "r"(a));
  return d;
}

__device__ __forceinline__ void wgmma_ss128_tn(float (&d)[64], uint64_t da, uint64_t db, int sd) {
  asm volatile("{\n.reg .pred p;\nsetp.ne.b32 p, %66, 0;\n"
    "wgmma.mma_async.sync.aligned.m64n128k16.f32.bf16.bf16 {%0, %1, %2, %3, %4, %5, %6, %7, %8, %9, %10, %11, %12, %13, %14, %15, %16, %17, %18, %19, %20, %21, %22, %23, %24, %25, %26, %27, %28, %29, %30, %31, %32, %33, %34, %35, %36, %37, %38, %39, %40, %41, %42, %43, %44, %45, %46, %47, %48, %49, %50, %51, %52, %53, %54, %55, %56, %57, %58, %59, %60, %61, %62, %63}, %64, %65, p, 1, 1, 1, 0;\n}\n"
    : "+f"(d[0]), "+f"(d[1]), "+f"(d[2]), "+f"(d[3]), "+f"(d[4]), "+f"(d[5]), "+f"(d[6]), "+f"(d[7]), "+f"(d[8]), "+f"(d[9]), "+f"(d[10]), "+f"(d[11]), "+f"(d[12]), "+f"(d[13]), "+f"(d[14]), "+f"(d[15]), "+f"(d[16]), "+f"(d[17]), "+f"(d[18]), "+f"(d[19]), "+f"(d[20]), "+f"(d[21]), "+f"(d[22]), "+f"(d[23]), "+f"(d[24]), "+f"(d[25]), "+f"(d[26]), "+f"(d[27]), "+f"(d[28]), "+f"(d[29]), "+f"(d[30]), "+f"(d[31]), "+f"(d[32]), "+f"(d[33]), "+f"(d[34]), "+f"(d[35]), "+f"(d[36]), "+f"(d[37]), "+f"(d[38]), "+f"(d[39]), "+f"(d[40]), "+f"(d[41]), "+f"(d[42]), "+f"(d[43]), "+f"(d[44]), "+f"(d[45]), "+f"(d[46]), "+f"(d[47]), "+f"(d[48]), "+f"(d[49]), "+f"(d[50]), "+f"(d[51]), "+f"(d[52]), "+f"(d[53]), "+f"(d[54]), "+f"(d[55]), "+f"(d[56]), "+f"(d[57]), "+f"(d[58]), "+f"(d[59]), "+f"(d[60]), "+f"(d[61]), "+f"(d[62]), "+f"(d[63])
    : "l"(da), "l"(db), "r"(sd));
}
__device__ __forceinline__ void wgmma_ss128_tt(float (&d)[64], uint64_t da, uint64_t db, int sd) {
  asm volatile("{\n.reg .pred p;\nsetp.ne.b32 p, %66, 0;\n"
    "wgmma.mma_async.sync.aligned.m64n128k16.f32.bf16.bf16 {%0, %1, %2, %3, %4, %5, %6, %7, %8, %9, %10, %11, %12, %13, %14, %15, %16, %17, %18, %19, %20, %21, %22, %23, %24, %25, %26, %27, %28, %29, %30, %31, %32, %33, %34, %35, %36, %37, %38, %39, %40, %41, %42, %43, %44, %45, %46, %47, %48, %49, %50, %51, %52, %53, %54, %55, %56, %57, %58, %59, %60, %61, %62, %63}, %64, %65, p, 1, 1, 1, 1;\n}\n"
    : "+f"(d[0]), "+f"(d[1]), "+f"(d[2]), "+f"(d[3]), "+f"(d[4]), "+f"(d[5]), "+f"(d[6]), "+f"(d[7]), "+f"(d[8]), "+f"(d[9]), "+f"(d[10]), "+f"(d[11]), "+f"(d[12]), "+f"(d[13]), "+f"(d[14]), "+f"(d[15]), "+f"(d[16]), "+f"(d[17]), "+f"(d[18]), "+f"(d[19]), "+f"(d[20]), "+f"(d[21]), "+f"(d[22]), "+f"(d[23]), "+f"(d[24]), "+f"(d[25]), "+f"(d[26]), "+f"(d[27]), "+f"(d[28]), "+f"(d[29]), "+f"(d[30]), "+f"(d[31]), "+f"(d[32]), "+f"(d[33]), "+f"(d[34]), "+f"(d[35]), "+f"(d[36]), "+f"(d[37]), "+f"(d[38]), "+f"(d[39]), "+f"(d[40]), "+f"(d[41]), "+f"(d[42]), "+f"(d[43]), "+f"(d[44]), "+f"(d[45]), "+f"(d[46]), "+f"(d[47]), "+f"(d[48]), "+f"(d[49]), "+f"(d[50]), "+f"(d[51]), "+f"(d[52]), "+f"(d[53]), "+f"(d[54]), "+f"(d[55]), "+f"(d[56]), "+f"(d[57]), "+f"(d[58]), "+f"(d[59]), "+f"(d[60]), "+f"(d[61]), "+f"(d[62]), "+f"(d[63])
    : "l"(da), "l"(db), "r"(sd));
}
__device__ __forceinline__ void wgmma_ss16_tn(float (&d)[8], uint64_t da, uint64_t db, int sd) {
  asm volatile("{\n.reg .pred p;\nsetp.ne.b32 p, %10, 0;\n"
    "wgmma.mma_async.sync.aligned.m64n16k16.f32.bf16.bf16 {%0, %1, %2, %3, %4, %5, %6, %7}, %8, %9, p, 1, 1, 1, 0;\n}\n"
    : "+f"(d[0]), "+f"(d[1]), "+f"(d[2]), "+f"(d[3]), "+f"(d[4]), "+f"(d[5]), "+f"(d[6]), "+f"(d[7])
    : "l"(da), "l"(db), "r"(sd));
}
__device__ __forceinline__ void wgmma_rs64_t_z(float (&d)[32], uint32_t a0, uint32_t a1, uint32_t a2, uint32_t a3, uint64_t db) {
  asm volatile("{\n.reg .pred p;\nsetp.ne.b32 p, 0, 0;\n"
    "wgmma.mma_async.sync.aligned.m64n64k16.f32.bf16.bf16 {%0, %1, %2, %3, %4, %5, %6, %7, %8, %9, %10, %11, %12, %13, %14, %15, %16, %17, %18, %19, %20, %21, %22, %23, %24, %25, %26, %27, %28, %29, %30, %31}, {%32, %33, %34, %35}, %36, p, 1, 1, 1;\n}\n"
    : "=f"(d[0]), "=f"(d[1]), "=f"(d[2]), "=f"(d[3]), "=f"(d[4]), "=f"(d[5]), "=f"(d[6]), "=f"(d[7]), "=f"(d[8]), "=f"(d[9]), "=f"(d[10]), "=f"(d[11]), "=f"(d[12]), "=f"(d[13]), "=f"(d[14]), "=f"(d[15]), "=f"(d[16]), "=f"(d[17]), "=f"(d[18]), "=f"(d[19]), "=f"(d[20]), "=f"(d[21]), "=f"(d[22]), "=f"(d[23]), "=f"(d[24]), "=f"(d[25]), "=f"(d[26]), "=f"(d[27]), "=f"(d[28]), "=f"(d[29]), "=f"(d[30]), "=f"(d[31])
    : "r"(a0), "r"(a1), "r"(a2), "r"(a3), "l"(db));
}
__device__ __forceinline__ void wgmma_rs64_t(float (&d)[32], uint32_t a0, uint32_t a1, uint32_t a2, uint32_t a3, uint64_t db) {
  asm volatile("{\n.reg .pred p;\nsetp.ne.b32 p, 1, 0;\n"
    "wgmma.mma_async.sync.aligned.m64n64k16.f32.bf16.bf16 {%0, %1, %2, %3, %4, %5, %6, %7, %8, %9, %10, %11, %12, %13, %14, %15, %16, %17, %18, %19, %20, %21, %22, %23, %24, %25, %26, %27, %28, %29, %30, %31}, {%32, %33, %34, %35}, %36, p, 1, 1, 1;\n}\n"
    : "+f"(d[0]), "+f"(d[1]), "+f"(d[2]), "+f"(d[3]), "+f"(d[4]), "+f"(d[5]), "+f"(d[6]), "+f"(d[7]), "+f"(d[8]), "+f"(d[9]), "+f"(d[10]), "+f"(d[11]), "+f"(d[12]), "+f"(d[13]), "+f"(d[14]), "+f"(d[15]), "+f"(d[16]), "+f"(d[17]), "+f"(d[18]), "+f"(d[19]), "+f"(d[20]), "+f"(d[21]), "+f"(d[22]), "+f"(d[23]), "+f"(d[24]), "+f"(d[25]), "+f"(d[26]), "+f"(d[27]), "+f"(d[28]), "+f"(d[29]), "+f"(d[30]), "+f"(d[31])
    : "r"(a0), "r"(a1), "r"(a2), "r"(a3), "l"(db));
}
__device__ __forceinline__ void wgmma_rs24_n(float (&d)[12], uint32_t a0, uint32_t a1, uint32_t a2, uint32_t a3, uint64_t db) {
  asm volatile("{\n.reg .pred p;\nsetp.ne.b32 p, 1, 0;\n"
    "wgmma.mma_async.sync.aligned.m64n24k16.f32.bf16.bf16 {%0, %1, %2, %3, %4, %5, %6, %7, %8, %9, %10, %11}, {%12, %13, %14, %15}, %16, p, 1, 1, 0;\n}\n"
    : "+f"(d[0]), "+f"(d[1]), "+f"(d[2]), "+f"(d[3]), "+f"(d[4]), "+f"(d[5]), "+f"(d[6]), "+f"(d[7]), "+f"(d[8]), "+f"(d[9]), "+f"(d[10]), "+f"(d[11])
    : "r"(a0), "r"(a1), "r"(a2), "r"(a3), "l"(db));
}

constexpr uint32_t SB0 = 0x400;
#define XNW 5
constexpr int NW = XNW, NKV = 4;
constexpr int SM_RES = 0;
constexpr int SM_W = 147456;
constexpr int SM_KV = SM_W + 5 * 8192;
constexpr int SM_S2 = SM_KV + NKV * KVB;
constexpr int SM_B1 = SM_S2 + 1024;
constexpr int SM_BAR = SM_B1 + 1152;
constexpr int SM_TOTAL = SM_BAR + 512;
enum { B_RESF = 0, B_RESE = 9, B_WF = 18, B_KVF = B_WF + NW, B_H7 = B_KVF + NKV, B_RED, B_ACC, B_O, B_COUNT = B_O + 3 };
enum { NB_H6 = 0, NB_WE = 1, NB_KVE = NB_WE + NW, NB_GEMM = NB_KVE + NKV, NB_QRDY, NB_EPI };
static_assert(NB_EPI + 3 <= 15, "named barriers");
static_assert(B_COUNT * 8 <= 512, "barriers");
struct Descs { uint64_t w, y, h, k0, kx, v; int dbg; };
static_assert(SM_TOTAL <= 232448, "smem");

#define XMASK 0xB5
constexpr uint32_t POLY_MASK = XMASK;
constexpr uint32_t MAGIC1 = 0x43DF, MAGIC2 = 0xBF15, MAGIC3 = 0xB9AF;

__device__ __forceinline__ int qkv_chunk(int p) {
  return (p % 3) * 9 + p / 3;
}

__device__ __forceinline__ float gelu_half(float w) {
  float p = fmaf(w * w, 8.0f * 0.044715f * 0.7978845608028654f, 2.0f * 0.7978845608028654f);
  float t = tanh_fast(w * p);
  return fmaf(w, t, w);
}

struct GState { int ws; uint32_t wph; bool lead; uint32_t ready; };
enum { EPI_NONE, EPI_GELU_G, EPI_GELU_S, EPI_RED };

template <int EPI>
__device__ __forceinline__ void epi_slice(const float (&a)[64], uint8_t* gp, uint32_t sp, int sl) {
  if (EPI == EPI_GELU_G || EPI == EPI_GELU_S) {
    uint32_t v[4];
#pragma unroll
    for (int j = 0; j < 4; j++) v[j] = pack_bf16(gelu_half(a[8 * sl + 2 * j]), gelu_half(a[8 * sl + 2 * j + 1]));
#pragma unroll
    for (int j = 0; j < 4; j++) {
      const int off = (2 * sl + (j >> 1)) * 128 + (j & 1) * 2048;
      if (EPI == EPI_GELU_G) stg32(gp + off, v[j]); else sts32(sp + off, v[j]);
    }
  } else if (EPI == EPI_RED) {
#pragma unroll
    for (int j = 0; j < 2; j++) {
      const int i = 2 * sl + j;
      asm volatile("red.global.add.v4.f32 [%0], {%1,%2,%3,%4};" ::"l"(gp + i * 512), "f"(a[4 * i]), "f"(a[4 * i + 1]), "f"(a[4 * i + 2]), "f"(a[4 * i + 3]) : "memory");
    }
  }
}

template <int PHASE>
__device__ __forceinline__ void gemm_kblock(float (&cur)[64], GState& st, const Descs& ds, uint64_t db, int first) {
  constexpr uint32_t bar = SB0 + SM_BAR;
  mbar_wait_unless(st.ready, bar + (B_WF + st.ws) * 8, st.wph);
  const uint64_t da = ds.w + (uint64_t)(uint32_t)(st.ws * 512);
  wg_fence();
#pragma unroll
  for (int u = 0; u < 4; u++) {
    if (PHASE == 0) wgmma_ss128_tn(cur, da + u * 128, db + u * 2, (u != 0) || !first);
    else wgmma_ss128_tt(cur, da + u * 128, db + u * 256, (u != 0) || !first);
  }
  wg_commit();
  if (++st.ws == NW) { st.ws = 0; st.wph ^= 1; }
  st.ready = mbar_test(bar + (B_WF + st.ws) * 8, st.wph);
}
__device__ __forceinline__ void gemm_release(const GState& st, int back) {
  int sl = st.ws - back; if (sl < 0) sl += NW;
  nb_arrive(NB_WE + sl, 160);
}

__device__ __forceinline__ void gemm_chunk_plain(float (&cur)[64], GState& st, const Descs& ds) {
#pragma unroll 1
  for (int kb = 0; kb < 9; kb++) {
    gemm_kblock<0>(cur, st, ds, ds.y + (uint64_t)(uint32_t)(kb * 1024), kb == 0);
    wg_wait<1>();
    if (kb > 0) gemm_release(st, 2);
  }
  wg_wait<0>();
  pin(cur);
  gemm_release(st, 1);
}

template <int PHASE, int EPI, bool DRAINED>
__device__ __forceinline__ void gemm_chunk(float (&cur)[64], float (&prev)[64], uint8_t* gp, uint32_t sp, GState& st, const Descs& ds,
                                           int c) {
  constexpr uint32_t bar = SB0 + SM_BAR;
  const uint64_t db = (PHASE == 0 ? ds.y : ds.h) + (uint64_t)(uint32_t)(st.ws >> 8);
#pragma unroll
  for (int kb = 0; kb < 9; kb++) {
    if (EPI == EPI_GELU_S) {
      if (kb == 8) {
        asm volatile("fence.proxy.async.shared::cta;" ::: "memory");
        nb_sync(NB_GEMM, 128);
      } else mbar_wait(bar + (B_RESF + kb) * 8, 0);
    }
    gemm_kblock<PHASE>(cur, st, ds, db + kb * 1024, kb == 0);
    if (DRAINED) { if (kb < 8) epi_slice<EPI>(prev, gp, sp, kb); }
    else { if (kb > 0) epi_slice<EPI>(prev, gp, sp, kb - 1); }
    if (!DRAINED || kb > 0) { wg_wait<1>(); gemm_release(st, 2); }
    if (!DRAINED && kb == 0) pin(prev);
    if (EPI == EPI_GELU_G) {
      if (kb == 7 && c == 7) nb_arrive(NB_H6, 160);
      if (kb == 7 && c == 8) { __syncwarp(); if (st.lead) mbar_arrive(bar + B_H7 * 8); }
      if (kb > 0 && c == 8 && st.lead) mbar_arrive(bar + (B_RESE + kb - 1) * 8);
    }
    if (EPI == EPI_RED && !DRAINED && c == 8) {
      if (kb > 0 && st.lead) mbar_arrive(bar + (B_RESE + kb - 1) * 8);
      if (kb == 8) { __syncwarp(); if (st.lead) mbar_arrive(bar + B_RED * 8); }
    }
  }
}
__device__ __forceinline__ void gemm_drain(float (&cur)[64], GState& st) {
  wg_wait<0>();
  pin(cur);
  gemm_release(st, 1);
}

__device__ __forceinline__ uint32_t exp2_pair_fix(float t0, float t1, uint32_t kc) {
  uint32_t z = __byte_perm(__float_as_uint(t0), __float_as_uint(t1), 0x6521);
  uint32_t mh;
  asm("lop3.b32 %0, %1, 0x007F007F, %2, 0xEA;" : "=r"(mh) : "r"(z), "r"(kc));
  uint32_t e = z - mh;
  uint32_t r;
  asm("fma.rn.bf16x2 %0, %1, %2, %3;" : "=r"(r) : "r"(z), "r"(mh), "r"(e));
  return r;
}
__device__ __forceinline__ void softmax_tile(const float (&s)[32], uint32_t (&p)[16], uint32_t kc) {
#pragma unroll
  for (int i = 0; i < 8; i++) {
    if ((POLY_MASK >> i) & 1) {
      p[2 * i + 0] = exp2_pair_fix(s[4 * i + 0], s[4 * i + 1], kc);
      p[2 * i + 1] = exp2_pair_fix(s[4 * i + 2], s[4 * i + 3], kc);
    } else {
      p[2 * i + 0] = pack_bf16(ex2f(s[4 * i + 0]), ex2f(s[4 * i + 1]));
      p[2 * i + 1] = pack_bf16(ex2f(s[4 * i + 2]), ex2f(s[4 * i + 3]));
    }
  }
}

__global__ void __launch_bounds__(512, 1)
main_kernel(const __grid_constant__ CUtensorMap tm_wqkv,
            const __grid_constant__ CUtensorMap tm_w1, const __grid_constant__ CUtensorMap tm_w2,
            const __grid_constant__ CUtensorMap tm_wo, const __grid_constant__ CUtensorMap tm_o,
            const __grid_constant__ Descs ds, const bf16* __restrict__ x, const bf16* __restrict__ b1,
            const bf16* __restrict__ b2, bf16* __restrict__ out) {
  extern __shared__ __align__(1024) uint8_t smem[];
  if (smem_u32(smem) != SB0) __trap();
  constexpr uint32_t sb = SB0;
  constexpr uint32_t bar = sb + SM_BAR;
  const int tid = threadIdx.x, lane = tid & 31;
  const int warp = __shfl_sync(0xffffffffu, tid >> 5, 0);
  const int r = blockIdx.x >> 3, g = blockIdx.x & 7;
  const int nq = (g < 3) ? 4 : 3;
  const int nA = nq + 9;

  if (warp == 12) {
    for (int i = lane; i < B_COUNT; i += 32)
      mbar_init(bar + i * 8, ((i >= B_RESE && i < B_WF) || i == B_H7 || i == B_RED) ? 4 : (i >= B_O ? 8 : 1));
    asm volatile("fence.mbarrier_init.release.cluster;" ::: "memory");
    __syncwarp();
    if (elect_one()) {
      const int c0 = qkv_chunk(g) * 64;
#pragma unroll
      for (int s = 0; s < NW; s++) {
        mbar_expect(bar + (B_WF + s) * 8, 8192);
        tma2d(sb + SM_W + s * 8192, &tm_wqkv, c0, s * 64, bar + (B_WF + s) * 8);
      }
    }
    __syncwarp();
  }
  {
    const int sub = lane & 7;
    uint4 xv[2][9];
#pragma unroll
    for (int ps = 0; ps < 2; ps++) {
      const int row = ps * 64 + warp * 4 + (lane >> 3);
      const uint4* xr = (const uint4*)(x + (size_t)(r * 128 + row) * D_) + sub;
#pragma unroll
      for (int j = 0; j < 9; j++) xv[ps][j] = __ldg(xr + j * 8);
    }
    if (tid < 256) {
      const int j = tid >> 6, grp = (tid >> 2) & 15, rw = tid & 3;
      const bool poly = (POLY_MASK >> (grp & 7)) & 1;
      uint32_t v = (rw == 1) ? 0x3F80u : (!poly ? 0u : (rw == 0 ? MAGIC1 : (rw == 2 ? MAGIC2 : MAGIC3)));
      v |= v << 16;
      *(uint4*)(g_kv + (size_t)((g + 8 * j) * NRT + r) * KVB + 4 * 2048 + grp * 128 + 64 + rw * 16) = make_uint4(v, v, v, v);
    } else if (tid < 256 + 72) {
      *(uint4*)(smem + SM_B1 + (tid - 256) * 16) = __ldg((const uint4*)(b1 + g * 576) + (tid - 256));
    }
#pragma unroll
    for (int ps = 0; ps < 2; ps++) {
      const int row = ps * 64 + warp * 4 + (lane >> 3);
      const uint32_t* xw = (const uint32_t*)xv[ps];
      float s0 = 0.f, s1 = 0.f;
#pragma unroll
      for (int j = 0; j < 36; j++) { s0 += bf_lo(xw[j]); s1 += bf_hi(xw[j]); }
      s0 += s1;
#pragma unroll
      for (int o = 4; o; o >>= 1) s0 += __shfl_xor_sync(~0u, s0, o);
      const float mu = s0 * (1.0f / D_);
      if (tid == 32 && mu != 123.f) TS(1 + 2 * ps);
      float q0 = 0.f, q1 = 0.f;
#pragma unroll
      for (int j = 0; j < 36; j++) { float a = bf_lo(xw[j]) - mu, b = bf_hi(xw[j]) - mu; q0 = fmaf(a, a, q0); q1 = fmaf(b, b, q1); }
      q0 += q1;
#pragma unroll
      for (int o = 4; o; o >>= 1) q0 += __shfl_xor_sync(~0u, q0, o);
      const float var = q0 * (1.0f / D_);
      const float rs1 = rsqrtf(var + 1e-5f);
      const float v2 = var * rs1 * rs1 + 1e-5f;
      const float rs2 = rsqrtf(v2);
      const float sc = rs1 * rs2, off = -mu * sc;
      uint8_t* dst = smem + SM_RES + row * 128 + ((sub ^ (row & 7)) << 4);
#pragma unroll
      for (int j = 0; j < 9; j++) {
        uint4 o;
        o.x = pack_bf16(fmaf(bf_lo(xw[4 * j + 0]), sc, off), fmaf(bf_hi(xw[4 * j + 0]), sc, off));
        o.y = pack_bf16(fmaf(bf_lo(xw[4 * j + 1]), sc, off), fmaf(bf_hi(xw[4 * j + 1]), sc, off));
        o.z = pack_bf16(fmaf(bf_lo(xw[4 * j + 2]), sc, off), fmaf(bf_hi(xw[4 * j + 2]), sc, off));
        o.w = pack_bf16(fmaf(bf_lo(xw[4 * j + 3]), sc, off), fmaf(bf_hi(xw[4 * j + 3]), sc, off));
        *(uint4*)(dst + j * 16384) = o;
      }
      if (tid == 32) TS(2 + 2 * ps);
      if (sub == 0) {
        float* s2p = (float*)(smem + SM_S2);
        s2p[row] = v2 * rs2;
        s2p[128 + row] = v2 * rs2 * (0.23570226039551584f * 1.4426950408889634f);
      }
    }
    asm volatile("fence.proxy.async.shared::cta;" ::: "memory");
  }
  __syncthreads();
  if (tid == 0) TS(0);

  if (warp >= 12) {
    asm volatile("setmaxnreg.dec.sync.aligned.u32 32;");
    const bool el = elect_one();
    if (warp == 12) {
      int s = 0;
      for (int ch = 0; ch < nA + 9; ch++) {
        const CUtensorMap* tm; int c0, k0;
        if (ch < nq) { tm = &tm_wqkv; c0 = qkv_chunk(g + 8 * ch) * 64; k0 = 0; }
        else if (ch < nA) { tm = &tm_w1; c0 = g * 576 + (ch - nq) * 64; k0 = 0; }
        else { int c = ch - nA + g + 1; if (c >= 9) c -= 9; tm = &tm_w2; c0 = c * 64; k0 = g * 576; }
#pragma unroll 1
        for (int kb = (ch == 0 ? NW : 0); kb < 9; kb++) {
          nb_sync(NB_WE + s, 160);
          if (el) {
            mbar_expect(bar + (B_WF + s) * 8, 8192);
            tma2d(sb + SM_W + s * 8192, tm, c0, k0 + kb * 64, bar + (B_WF + s) * 8);
          }
          if (++s == NW) s = 0;
        }
      }
#pragma unroll 1
      for (int i = 0; i < 18; i++) {
        nb_sync(NB_WE + s, 160);
        if (el) {
          mbar_expect(bar + (B_WF + s) * 8, 8192);
          tma2d(sb + SM_W + s * 8192, &tm_wo, (i & 1) ? 512 : g * 64, (i >> 1) * 64, bar + (B_WF + s) * 8);
        }
        if (++s == NW) s = 0;
      }
#pragma unroll 1
      for (int i = 0; i < NW; i++) { nb_sync(NB_WE + s, 160); if (++s == NW) s = 0; }
    } else if (warp == 13) {
      for (int j = 0; j < 4; j++) {
        const int h = g + 8 * j;
        const int c_lo = (h * 18) >> 6, c_hi = (h * 18 + 17) >> 6;
        if (lane < 6) flag_wait(&g_flags.qkv[(lane >> 1) * 9 + ((lane & 1) ? c_hi : c_lo)], NRT);
        else if (lane == 6) flag_wait(&g_flags.qkv[27 + g / 2], 2 * NRT);
        __syncwarp();
        nb_arrive(NB_QRDY, 288);
        if (el) fence_async_all();
        const uint8_t* src = g_kv + (size_t)h * NRT * KVB;
#pragma unroll 1
        for (int t = 0; t < NRT; t++) {
          const int s = t & (NKV - 1);
          if (j > 0 || t >= NKV) nb_sync(NB_KVE + s, 288);
          if (el) {
            mbar_expect(bar + (B_KVF + s) * 8, KVB);
            bulk_ld(sb + SM_KV + s * KVB, src + (size_t)t * KVB, KVB, bar + (B_KVF + s) * 8);
          }
        }
      }
      for (int s = 0; s < NKV; s++) nb_sync(NB_KVE + s, 288);
    } else if (warp == 14) {
      if (el) flag_add(&g_flags.qkv[27 + g / 2]);
      nb_sync(NB_H6, 160);
      if (el) {
        flag_wait(&g_flags.zero[r], NG * 8);
        const uint8_t* src = g_h + (size_t)(r * 72 + g * 9) * 16384;
        asm volatile("fence.acq_rel.gpu;" ::: "memory"); fence_async_all();
        for (int kb = 0; kb < 8; kb++) {
          mbar_wait_slow(bar + (B_RESE + kb) * 8, 0);
          if (kb == 7) { mbar_wait_slow(bar + B_H7 * 8, 0); asm volatile("fence.acq_rel.gpu;" ::: "memory"); fence_async_all(); }
          mbar_expect(bar + (B_RESF + kb) * 8, 16384);
          bulk_ld(sb + SM_RES + kb * 16384, src + (size_t)kb * 16384, 16384, bar + (B_RESF + kb) * 8);
        }
        mbar_wait_sleep(bar + B_RESE * 8, 1);
        for (int kb = 0; kb < 9; kb++) {
          if (!(kb & 1) && kb < 8) { flag_wait(&g_flags.ocnt[r * 4 + (kb >> 1)], (kb == 6) ? NG * 8 : NG); fence_async_all(); }
          mbar_wait(bar + (B_RESE + kb) * 8, kb < 8 ? 1 : 0);
          mbar_expect(bar + (B_RESF + kb) * 8, 16384);
          tma2d(sb + SM_RES + kb * 16384, &tm_o, kb * 64, r * 128, bar + (B_RESF + kb) * 8);
        }
        flag_wait(&g_flags.red[r], NG);
        mbar_arrive(bar + B_ACC * 8);
        if (atomicAdd(&g_flags.done, 1u) == NRT * NG - 1) {
          unsigned* f = (unsigned*)&g_flags;
          for (int i = 0; i < (int)(sizeof(Flags) / 4); i++) f[i] = 0u;
        }
      }
    } else {
      for (int ch = 0; ch < nq; ch++) {
        nb_sync(NB_EPI + ch, 160);
        if (el) flag_add(&g_flags.qkv[qkv_chunk(g + 8 * ch)]);
        __syncwarp();
      }
      if (el) {
        for (int j = 0; j < 3; j++) {
          mbar_wait_sleep(bar + (B_O + j) * 8, 0);
          flag_add(&g_flags.ocnt[r * 4 + j]);
        }
        mbar_wait_slow(bar + B_RED * 8, 0);
        flag_add(&g_flags.red[r]);
      }
    }
  } else if (warp >= 8) {
    asm volatile("setmaxnreg.inc.sync.aligned.u32 176;");
    const int w = warp - 8, gq = lane >> 2, t = lane & 3;
    if (tid == 256) TS(5);
    GState st{0, 0u, lane == 0, 0u};
    float d0[64], d1[64];
#pragma unroll
    for (int i = 0; i < 64; i++) { d0[i] = 0.f; d1[i] = 0.f; }
    pin(d0); pin(d1);
    if (tid == 256) TS(7);
#pragma unroll 1
    for (int ch = 0; ch <= nq; ch++) {
      gemm_chunk_plain(d0, st, ds);
      if (tid == 256 && ch == 0) TS(23);
      if (ch == nq) break;
      const int cq = qkv_chunk(g + 8 * ch);
      const int part = cq / 9;
      const uint32_t s2a = sb + SM_S2 + (part == 0 ? 512 : 0) + t * 8;
      uint8_t* pp[2];
#pragma unroll
      for (int hf = 0; hf < 2; hf++) {
        const int jj = (cq - part * 9) * 64 + w * 16 + hf * 8 + gq;
        const int head = jj / 18, dim = jj - head * 18;
        uint8_t* base; int off;
        if (part == 0) { base = g_q + (size_t)(head * NRT + r) * QB; off = (dim >> 3) * 2048 + (dim & 7) * 16; }
        else {
          base = g_kv + (size_t)(head * NRT + r) * KVB;
          off = (dim < 16) ? ((part - 1) * 2 + (dim >> 3)) * 2048 + (dim & 7) * 16 : 4 * 2048 + ((part - 1) * 2 + dim - 16) * 16;
        }
        pp[hf] = base + off + t * 4;
      }
      float2 sv[16];
#pragma unroll
      for (int i = 0; i < 16; i++) asm volatile("ld.shared.v2.f32 {%0,%1}, [%2];" : "=f"(sv[i].x), "=f"(sv[i].y) : "r"(s2a + i * 32));
#pragma unroll
      for (int i = 0; i < 16; i++) {
        stg32(pp[0] + i * 128, pack_bf16(d0[4 * i + 0] * sv[i].x, d0[4 * i + 1] * sv[i].y));
        stg32(pp[1] + i * 128, pack_bf16(d0[4 * i + 2] * sv[i].x, d0[4 * i + 3] * sv[i].y));
      }
      nb_arrive(NB_EPI + ch, 160);
      if (tid == 256) TS(8 + ch);
    }
    auto bias_move = [&](int c) {
      const bf16* bs = (const bf16*)(smem + SM_B1) + c * 64 + w * 16 + gq;
      const float b0 = 0.5f * __bfloat162float(bs[0]), b1v = 0.5f * __bfloat162float(bs[8]);
#pragma unroll
      for (int i = 0; i < 64; i++) d1[i] = fmaf(d0[i], 0.5f, (i & 2) ? b1v : b0);
      pin(d1);
    };
    uint8_t* hp = g_h + (size_t)(r * 72 + g * 9) * 16384 + (2 * w) * 2048 + lane * 4;
#pragma unroll 1
    for (int c = 1; c < 9; c++) {
      bias_move(c - 1);
      gemm_chunk<0, EPI_GELU_G, true>(d0, d1, hp, 0u, st, ds, c);
      hp += 16384;
      gemm_drain(d0, st);
      if (tid == 256 && !(c & 1)) TS(12 + (c >> 1));
    }
    bias_move(8);
    nb_sync(NB_GEMM, 128);
    auto red_ptr = [&](int c2) {
      int c = c2 + g + 1; if (c >= 9) c -= 9;
      return (uint8_t*)(g_acc + (size_t)(r * 9 + c) * 8192 + w * 2048 + lane * 4);
    };
    gemm_chunk<1, EPI_GELU_S, true>(d0, d1, nullptr, sb + SM_RES + 8 * 16384 + (2 * w) * 2048 + lane * 4, st, ds, 0);
    gemm_drain(d0, st);
    if (tid == 256) TS(17);
#pragma unroll 1
    for (int c2 = 1; c2 < 9; c2 += 2) {
      gemm_chunk<1, EPI_RED, true>(d1, d0, red_ptr(c2 - 1), 0u, st, ds, 0);
      gemm_chunk<1, EPI_RED, false>(d0, d1, red_ptr(c2), 0u, st, ds, c2 + 1);
      gemm_drain(d0, st);
      if (tid == 256) TS(18 + (c2 >> 1));
    }
    if (st.lead) mbar_arrive(bar + (B_RESE + 8) * 8);
    float d2[8];
#pragma unroll
    for (int i = 0; i < 8; i++) d2[i] = 0.f;
    pin(d2);
#pragma unroll 1
    for (int kb = 0; kb < 9; kb++) {
      mbar_wait(bar + (B_RESF + kb) * 8, kb < 8 ? 1 : 0);
      const uint64_t db = ds.y + (uint64_t)(uint32_t)(kb * 1024);
      gemm_kblock<0>(d0, st, ds, db, 0);
      wg_wait<1>();
      if (kb > 0) gemm_release(st, 2);
      mbar_wait_unless(st.ready, bar + (B_WF + st.ws) * 8, st.wph);
      const uint64_t da = ds.w + (uint64_t)(uint32_t)(st.ws * 512), db2 = db + (uint64_t)(uint32_t)(g * 128);
      wg_fence();
#pragma unroll
      for (int u = 0; u < 4; u++) wgmma_ss16_tn(d2, da + u * 128, db2 + u * 2, 1);
      wg_commit();
      if (++st.ws == NW) { st.ws = 0; st.wph ^= 1; }
      st.ready = mbar_test(bar + (B_WF + st.ws) * 8, st.wph);
      wg_wait<1>();
      gemm_release(st, 2);
    }
    mbar_wait(bar + B_ACC * 8, 0);
    {
      const float4* ap = (const float4*)(g_acc + (size_t)(r * 9 + g) * 8192 + w * 2048 + lane * 4);
      const float4* ap2 = (const float4*)(g_acc + (size_t)(r * 9 + 8) * 8192 + w * 2048 + (2 * g) * 128 + lane * 4);
      float4 av[18];
#pragma unroll
      for (int i = 0; i < 16; i++) av[i] = __ldcg(ap + i * 32);
      av[16] = __ldcg(ap2); av[17] = __ldcg(ap2 + 32);
      wg_wait<0>();
      pin(d0); pin(d2);
      gemm_release(st, 1);
      uint8_t* op = (uint8_t*)(out + (size_t)(r * 128 + gq) * D_ + g * 64 + w * 16 + t * 2);
#pragma unroll
      for (int i = 0; i < 16; i++) {
        stg32(op + i * (8 * D_ * 2), movm(pack_bf16(d0[4 * i] + av[i].x, d0[4 * i + 1] + av[i].y)));
        stg32(op + i * (8 * D_ * 2) + 16, movm(pack_bf16(d0[4 * i + 2] + av[i].z, d0[4 * i + 3] + av[i].w)));
      }
      uint8_t* op2 = (uint8_t*)(out + (size_t)(r * 128 + g * 16 + gq) * D_ + 512 + w * 16 + t * 2);
#pragma unroll
      for (int i = 0; i < 2; i++) {
        stg32(op2 + i * (8 * D_ * 2), movm(pack_bf16(d2[4 * i] + av[16 + i].x, d2[4 * i + 1] + av[16 + i].y)));
        stg32(op2 + i * (8 * D_ * 2) + 16, movm(pack_bf16(d2[4 * i + 2] + av[16 + i].z, d2[4 * i + 3] + av[16 + i].w)));
      }
    }
    if (tid == 256) TS(22);
  } else {
    asm volatile("setmaxnreg.inc.sync.aligned.u32 152;");
    const int gq = lane >> 2, t = lane & 3;
    {
      const int i = 2 * g + (warp & 1);
#pragma unroll 1
      for (int c = 0; c < 9; c++) {
        const int col = c * 64 + (warp >> 1) * 16;
        const uint32_t* xp = (const uint32_t*)(x + (size_t)(r * 128 + i * 8 + gq) * D_ + col) + t;
        const uint32_t x0 = movm(__ldg(xp)), x1 = movm(__ldg(xp + 4));
        const float c0 = __bfloat162float(b2[col + gq]), c1 = __bfloat162float(b2[col + 8 + gq]);
        *(float4*)(g_acc + (size_t)(r * 9 + c) * 8192 + (warp >> 1) * 2048 + i * 128 + lane * 4) =
            make_float4(bf_lo(x0) + c0, bf_hi(x0) + c0, bf_lo(x1) + c1, bf_hi(x1) + c1);
      }
      __syncwarp();
      if (lane == 0) flag_add(&g_flags.zero[r]);
    }
    uint32_t ph = 0;
    const uint32_t zr = (uint32_t)(ds.dbg >> 30), kc = 0x9F809F80u + zr;
#pragma unroll 1
    for (int j = 0; j < 4; j++) {
      const int h = g + 8 * j;
      nb_sync(NB_QRDY, 288);
      if ((tid & 127) == 0) TS(24 + (tid >> 7) * 8 + 2 * j);
      uint32_t q0, q1, q2, q3, q4, q5;
      {
        const uint8_t* qp = g_q + (size_t)(h * NRT + r) * QB + (warp * 2) * 128 + lane * 4;
        q0 = __ldcg((const uint32_t*)(qp));
        q1 = __ldcg((const uint32_t*)(qp + 128));
        q2 = __ldcg((const uint32_t*)(qp + 2048));
        q3 = __ldcg((const uint32_t*)(qp + 2048 + 128));
        q4 = (lane < 8) ? __ldcg((const uint32_t*)(qp + 4096)) : 0u;
        q5 = (lane < 8) ? __ldcg((const uint32_t*)(qp + 4096 + 128)) : 0u;
        q0 = movm(q0); q1 = movm(q1); q2 = movm(q2); q3 = movm(q3); q4 = movm(q4); q5 = movm(q5);
        if (t == 2) { q4 = 0x00003F80u; q5 = 0x00003F80u; }
        if (t == 3) { q4 = 0x3F803F80u; q5 = 0x3F803F80u; }
      }
      float o[12], sa[32], sbb[32];
      uint32_t pa[16], pb[16];
#pragma unroll
      for (int i = 0; i < 12; i++) o[i] = 0.f;
      pin(o);
#define ISSUE_S(S, off) { wgmma_rs64_t_z(S, q0, q1, q2, q3, dk0 + (off)); wgmma_rs64_t(S, q4, q5, zr, zr, dkx + (off)); }
#define ISSUE_PV(P, off) { _Pragma("unroll") for (int k = 0; k < 4; k++) wgmma_rs24_n(o, P[4 * k], P[4 * k + 1], P[4 * k + 2], P[4 * k + 3], dv + ((off) + k * 16)); }
      {
        const uint64_t dk0 = ds.k0, dkx = ds.kx;
        mbar_wait(bar + B_KVF * 8, ph);
        wg_fence();
        ISSUE_S(sa, 0);
        wg_commit();
        wg_wait<0>();
      }
      if (tid == 0 && j == 0) TS(6);
#pragma unroll 1
      for (int s4 = 0; s4 < NRT / NKV; s4++) {
        const uint64_t z64 = (uint64_t)(uint32_t)(s4 >> 8);
        const uint64_t dk0 = ds.k0 + z64, dkx = ds.kx + z64, dv = ds.v + z64;
#pragma unroll
        for (int sl = 0; sl < NKV; sl++) {
          constexpr int SS = KVB / 16;
          const int nx = (sl + 1) % NKV;
          if (sl == NKV - 1) ph ^= 1;
          pin(sa);
          wg_fence();
          ISSUE_S(sbb, sl * SS + 64);
          wg_commit();
          uint32_t rdy = mbar_test(bar + (B_KVF + nx) * 8, ph);
          softmax_tile(sa, pa, kc);
          pin(pa);
          wg_fence();
          ISSUE_PV(pa, sl * SS);
          wg_commit();
          if (sl == NKV - 1) rdy |= (uint32_t)(s4 + 1 == NRT / NKV);
          mbar_wait_unless(rdy, bar + (B_KVF + nx) * 8, ph);
          wg_wait<1>();
          pin(sbb);
          if (sl > 0 || s4 > 0) nb_arrive(NB_KVE + (sl + NKV - 1) % NKV, 288);
          wg_fence();
          ISSUE_S(sa, nx * SS);
          wg_commit();
          softmax_tile(sbb, pb, kc);
          pin(pb);
          wg_fence();
          ISSUE_PV(pb, sl * SS + 64);
          wg_commit();
          wg_wait<1>();
        }
      }
      wg_wait<0>();
      pin(o);
      nb_arrive(NB_KVE + NKV - 1, 288);
      const float l0 = __shfl_sync(~0u, o[9], (lane & ~3) + 2), l1 = __shfl_sync(~0u, o[11], (lane & ~3) + 2);
      const float i0 = __frcp_rn(l0), i1 = __frcp_rn(l1);
      uint32_t* op = (uint32_t*)(g_o + (size_t)(r * 128 + warp * 16 + gq) * D_ + h * 18) + t;
      op[0] = pack_bf16(o[0] * i0, o[1] * i0);
      op[4] = pack_bf16(o[4] * i0, o[5] * i0);
      op[8 * 288] = pack_bf16(o[2] * i1, o[3] * i1);
      op[8 * 288 + 4] = pack_bf16(o[6] * i1, o[7] * i1);
      if (t == 1) {
        op[7] = pack_bf16(o[8] * i0, o[9] * i0);
        op[8 * 288 + 7] = pack_bf16(o[10] * i1, o[11] * i1);
      }
      __syncwarp();
      if (lane == 0) { if (j < 3) mbar_arrive(bar + (B_O + j) * 8); else flag_add(&g_flags.ocnt[r * 4 + 3]); }
      if ((tid & 127) == 0) TS(24 + (tid >> 7) * 8 + 2 * j + 1);
    }
  }
}

typedef CUresult (*enc_fn)(CUtensorMap*, CUtensorMapDataType, cuuint32_t, void*, const cuuint64_t*, const cuuint64_t*,
                           const cuuint32_t*, const cuuint32_t*, CUtensorMapInterleave, CUtensorMapSwizzle,
                           CUtensorMapL2promotion, CUtensorMapFloatOOBfill);
static void make_map(enc_fn enc, CUtensorMap* tm, const void* p, int cols, int rows, int bc, int br) {
  cuuint64_t gd[2] = {(cuuint64_t)cols, (cuuint64_t)rows};
  cuuint64_t gs[1] = {(cuuint64_t)cols * 2};
  cuuint32_t bx[2] = {(cuuint32_t)bc, (cuuint32_t)br};
  cuuint32_t es[2] = {1, 1};
  enc(tm, CU_TENSOR_MAP_DATA_TYPE_BFLOAT16, 2, (void*)p, gd, gs, bx, es, CU_TENSOR_MAP_INTERLEAVE_NONE,
      CU_TENSOR_MAP_SWIZZLE_128B, CU_TENSOR_MAP_L2_PROMOTION_L2_256B, CU_TENSOR_MAP_FLOAT_OOB_FILL_NONE);
}

extern "C" void kernel_launch(void* const* d_in, const int* in_sizes, int n_in, void* d_out, int out_size) {
  const bf16* x = (const bf16*)d_in[0];
  const bf16* wqkv = (const bf16*)d_in[1];
  const bf16* wo = (const bf16*)d_in[2];
  const bf16* w1 = (const bf16*)d_in[4];
  const bf16* b1 = (const bf16*)d_in[5];
  const bf16* w2 = (const bf16*)d_in[6];
  const bf16* b2 = (const bf16*)d_in[7];
  static enc_fn enc = nullptr;
  static void* po = nullptr;
  if (!enc) {
    void* fn = nullptr;
    cudaDriverEntryPointQueryResult qr;
    cudaGetDriverEntryPoint("cuTensorMapEncodeTiled", &fn, cudaEnableDefault, &qr);
    enc = (enc_fn)fn;
    cudaGetSymbolAddress(&po, g_o);
    cudaFuncSetAttribute(main_kernel, cudaFuncAttributeMaxDynamicSharedMemorySize, SM_TOTAL);
  }
  CUtensorMap tm_wqkv, tm_w1, tm_w2, tm_wo, tm_o;
  make_map(enc, &tm_o, po, D_, S_, 64, 128);
  make_map(enc, &tm_wqkv, wqkv, 3 * D_, D_, 64, 64);
  make_map(enc, &tm_w1, w1, F_, D_, 64, 64);
  make_map(enc, &tm_w2, w2, D_, F_, 64, 64);
  make_map(enc, &tm_wo, wo, D_, D_, 64, 64);
  auto mk = [](uint32_t addr, uint32_t lbo, uint32_t sbo, uint32_t swz) {
    return ((uint64_t)desc_hi(sbo, swz) << 32) | (uint64_t)((addr >> 4) | desc_lbo(lbo));
  };
  Descs ds;
  ds.w = mk(SB0 + SM_W, 0, 1024, 1);
  ds.y = mk(SB0 + SM_RES, 0, 1024, 1);
  ds.h = mk(SB0 + SM_RES, 2048, 128, 0);
  ds.k0 = mk(SB0 + SM_KV, 2048, 128, 0);
  ds.kx = mk(SB0 + SM_KV + 8192, 0, 128, 0);
  ds.v = mk(SB0 + SM_KV + 4096, 128, 2048, 0);
  ds.dbg = 0;
  main_kernel<<<NRT * NG, 512, SM_TOTAL>>>(tm_wqkv, tm_w1, tm_w2, tm_wo, tm_o, ds, x, b1, b2, (bf16*)d_out);
}
```

```cpp
#include <cuda_runtime.h>
#include <cuda_bf16.h>
#include <cuda.h>
#include <stdint.h>

typedef __nv_bfloat16 bf16;

constexpr int S_ = 2048, D_ = 576, F_ = 4608, H_ = 32, DH_ = 18;
constexpr int NRT = 16;
constexpr int NG = 8;

constexpr int KVB = 10240;
constexpr int QB = 6144;
__device__ __align__(1024) uint8_t g_y[NRT * 147456];
__device__ __align__(1024) uint8_t g_o[NRT * 147456];
__device__ __align__(1024) float2 g_st[S_];
__device__ __align__(1024) uint8_t g_q[H_ * NRT * QB];
__device__ __align__(1024) uint8_t g_kv[H_ * NRT * KVB];
__device__ __align__(1024) uint8_t g_h[NRT * 72 * 16384];
__device__ __align__(1024) float g_acc[NRT * 9 * 8192];
struct __align__(128) Flag { unsigned v; unsigned pad[31]; };
struct Flags {
  Flag ln[NRT];
  Flag red[NRT];
  Flag ocnt[NRT * 4];
  Flag qkv[32];
  Flag done;
};
__device__ Flags g_flags;
__device__ unsigned g_epoch;
__device__ __align__(1024) uint2 g_kn[H_ * 128];
#define TSC(cond, idx) do {} while (0)

__device__ __forceinline__ uint32_t smem_u32(const void* p) { return (uint32_t)__cvta_generic_to_shared(p); }
__device__ __forceinline__ void wg_fence() { asm volatile("wgmma.fence.sync.aligned;" ::: "memory"); }
__device__ __forceinline__ void wg_commit() { asm volatile("wgmma.commit_group.sync.aligned;" ::: "memory"); }
template <int N> __device__ __forceinline__ void wg_wait() { asm volatile("wgmma.wait_group.sync.aligned %0;" ::"n"(N) : "memory"); }
template <int N> __device__ __forceinline__ void pin(float (&d)[N]) {
#pragma unroll
  for (int i = 0; i < N; i++) asm volatile("" : "+f"(d[i])::"memory");
}
template <int N> __device__ __forceinline__ void pin(uint32_t (&d)[N]) {
#pragma unroll
  for (int i = 0; i < N; i++) asm volatile("" : "+r"(d[i])::"memory");
}
__device__ __forceinline__ uint64_t mkdesc(uint32_t lo, uint32_t hi) { return ((uint64_t)hi << 32) | lo; }
__host__ __device__ constexpr uint32_t desc_lbo(uint32_t lbo) { return (lbo >> 4) << 16; }
__host__ __device__ constexpr uint32_t desc_hi(uint32_t sbo, uint32_t swz) { return (sbo >> 4) | (swz << 30); }

__device__ __forceinline__ void mbar_init(uint32_t bar, int cnt) { asm volatile("mbarrier.init.shared::cta.b64 [%0], %1;" ::"r"(bar), "r"(cnt)); }
__device__ __forceinline__ void mbar_expect(uint32_t bar, uint32_t bytes) {
  asm volatile("mbarrier.arrive.expect_tx.shared::cta.b64 _, [%0], %1;" ::"r"(bar), "r"(bytes) : "memory");
}
__device__ __forceinline__ void mbar_arrive(uint32_t bar) { asm volatile("mbarrier.arrive.shared::cta.b64 _, [%0];" ::"r"(bar) : "memory"); }
__device__ __forceinline__ uint32_t mbar_test(uint32_t bar, uint32_t ph) {
  uint32_t ok;
  asm volatile("{\n.reg .pred p;\nmbarrier.test_wait.parity.shared::cta.b64 p, [%1], %2;\nselp.u32 %0,1,0,p;\n}" : "=r"(ok) : "r"(bar), "r"(ph) : "memory");
  return ok;
}
__device__ __forceinline__ void mbar_wait(uint32_t bar, uint32_t ph) {
  asm volatile("{\n.reg .pred p;\nMW_LOOP:\nmbarrier.try_wait.parity.shared::cta.b64 p, [%0], %1;\n@!p bra MW_LOOP;\n}" ::"r"(bar), "r"(ph) : "memory");
}
__device__ __forceinline__ void mbar_wait_nap(uint32_t bar, uint32_t ph) {
  asm volatile("{\n.reg .pred p;\nMN_LOOP:\nmbarrier.try_wait.parity.shared::cta.b64 p, [%0], %1;\n@p bra MN_DONE;\nnanosleep.u32 100;\nbra MN_LOOP;\nMN_DONE:\n}" ::"r"(bar), "r"(ph) : "memory");
}
__device__ __forceinline__ void mbar_wait_unless(uint32_t ok, uint32_t bar, uint32_t ph) {
  asm volatile(
      "{\n.reg .pred p;\n"
      "setp.ne.u32 p, %2, 0;\n"
      "@p bra MW_DONE;\n"
      "MW_LOOP:\nmbarrier.try_wait.parity.shared::cta.b64 p, [%0], %1;\n@!p bra MW_LOOP;\n"
      "MW_DONE:\n}" ::"r"(bar), "r"(ph), "r"(ok) : "memory");
}
__device__ __forceinline__ void mbar_wait_slow(uint32_t bar, uint32_t ph) {
  asm volatile(
      "{\n.reg .pred p;\n.reg .u32 c;\n"
      "mov.u32 c, 0;\n"
      "MS_LOOP:\n"
      "mbarrier.try_wait.parity.shared::cta.b64 p, [%0], %1;\n"
      "@p bra MS_DONE;\n"
      "nanosleep.u32 64;\n"
      "add.u32 c, c, 1;\n"
      "setp.lt.u32 p, c, 1000000;\n"
      "@p bra MS_LOOP;\n"
      "trap;\n"
      "MS_DONE:\n}" ::"r"(bar), "r"(ph) : "memory");
}
__device__ __forceinline__ void mbar_wait_sleep(uint32_t bar, uint32_t ph) {
  asm volatile(
      "{\n.reg .pred p;\n.reg .u32 c;\n"
      "mov.u32 c, 0;\n"
      "MS_LOOP:\n"
      "mbarrier.try_wait.parity.shared::cta.b64 p, [%0], %1;\n"
      "@p bra MS_DONE;\n"
      "nanosleep.u32 250;\n"
      "add.u32 c, c, 1;\n"
      "setp.lt.u32 p, c, 1000000;\n"
      "@p bra MS_LOOP;\n"
      "trap;\n"
      "MS_DONE:\n}" ::"r"(bar), "r"(ph) : "memory");
}
__device__ __forceinline__ void nb_sync(int id, int n) { asm volatile("bar.sync %0, %1;" ::"r"(id), "r"(n) : "memory"); }
__device__ __forceinline__ void nb_arrive(int id, int n) { asm volatile("bar.arrive %0, %1;" ::"r"(id), "r"(n) : "memory"); }
__device__ __forceinline__ void st32(void* p, uint32_t v) { asm volatile("st.b32 [%0], %1;" ::"l"(p), "r"(v) : "memory"); }
__device__ __forceinline__ void stg32(void* p, uint32_t v) { asm volatile("st.global.b32 [%0], %1;" ::"l"(p), "r"(v) : "memory"); }
__device__ __forceinline__ void sts32(uint32_t a, uint32_t v) { asm volatile("st.shared.b32 [%0], %1;" ::"r"(a), "r"(v) : "memory"); }
__device__ __forceinline__ bool elect_one() {
  uint32_t p;
  asm volatile("{\n.reg .pred q;\nelect.sync _|q, 0xffffffff;\nselp.u32 %0, 1, 0, q;\n}" : "=r"(p));
  return p != 0;
}
__device__ __forceinline__ void tma2d(uint32_t dst, const CUtensorMap* tm, int c0, int c1, uint32_t bar) {
  asm volatile("cp.async.bulk.tensor.2d.shared::cluster.global.mbarrier::complete_tx::bytes [%0], [%1, {%3, %4}], [%2];" ::"r"(dst), "l"(tm), "r"(bar), "r"(c0), "r"(c1) : "memory");
}
__device__ __forceinline__ uint64_t policy_evict_first() {
  uint64_t p;
  asm volatile("createpolicy.fractional.L2::evict_first.b64 %0, 1.0;" : "=l"(p));
  return p;
}
__device__ __forceinline__ void tma2d_h(uint32_t dst, const CUtensorMap* tm, int c0, int c1, uint32_t bar, uint64_t pol) {
  asm volatile("cp.async.bulk.tensor.2d.shared::cluster.global.mbarrier::complete_tx::bytes.L2::cache_hint [%0], [%1, {%3, %4}], [%2], %5;" ::"r"(dst), "l"(tm), "r"(bar), "r"(c0), "r"(c1), "l"(pol) : "memory");
}
__device__ __forceinline__ void bulk_ld_h(uint32_t dst, const void* src, uint32_t bytes, uint32_t bar, uint64_t pol) {
  asm volatile("cp.async.bulk.shared::cluster.global.mbarrier::complete_tx::bytes.L2::cache_hint [%0], [%1], %2, [%3], %4;" ::"r"(dst), "l"(src), "r"(bytes), "r"(bar), "l"(pol) : "memory");
}
__device__ __forceinline__ void bulk_ld(uint32_t dst, const void* src, uint32_t bytes, uint32_t bar) {
  asm volatile("cp.async.bulk.shared::cluster.global.mbarrier::complete_tx::bytes [%0], [%1], %2, [%3];" ::"r"(dst), "l"(src), "r"(bytes), "r"(bar) : "memory");
}
__device__ __forceinline__ void l2_prefetch(const void* p, uint32_t bytes) {
  asm volatile("cp.async.bulk.prefetch.L2.global [%0], %1;" ::"l"(p), "r"(bytes) : "memory");
}
__device__ __forceinline__ void flag_wait(const Flag* p, unsigned target) {
  asm volatile(
      "{\n.reg .pred p;\n.reg .u32 c, v;\n"
      "mov.u32 c, 0;\n"
      "FW_LOOP:\n"
      "ld.acquire.gpu.global.u32 v, [%0];\n"
      "setp.ge.u32 p, v, %1;\n"
      "@p bra FW_DONE;\n"
      "nanosleep.u32 100;\n"
      "add.u32 c, c, 1;\n"
      "setp.lt.u32 p, c, 4000000;\n"
      "@p bra FW_LOOP;\n"
      "trap;\n"
      "FW_DONE:\n}" ::"l"(p), "r"(target) : "memory");
}
__device__ __forceinline__ void flag_wait_sleep(const Flag* p, unsigned target) {
  asm volatile(
      "{\n.reg .pred p;\n.reg .u32 c, v;\n"
      "mov.u32 c, 0;\n"
      "FW_LOOP:\n"
      "ld.acquire.gpu.global.u32 v, [%0];\n"
      "setp.ge.u32 p, v, %1;\n"
      "@p bra FW_DONE;\n"
      "nanosleep.u32 500;\n"
      "add.u32 c, c, 1;\n"
      "setp.lt.u32 p, c, 1000000;\n"
      "@p bra FW_LOOP;\n"
      "trap;\n"
      "FW_DONE:\n}" ::"l"(p), "r"(target) : "memory");
}
__device__ __forceinline__ void flag_add(Flag* p) {
  asm volatile("fence.acq_rel.gpu;\nred.relaxed.gpu.global.add.u32 [%0], 1;" ::"l"(p) : "memory");
}
__device__ __forceinline__ void fence_async_all() { asm volatile("fence.proxy.async;" ::: "memory"); }
__device__ __forceinline__ uint32_t pack_bf16(float lo, float hi) {
  uint32_t r;
  asm("cvt.rn.bf16x2.f32 %0, %1, %2;" : "=r"(r) : "f"(hi), "f"(lo));
  return r;
}
__device__ __forceinline__ float ex2f(float x) { float y; asm("ex2.approx.ftz.f32 %0, %1;" : "=f"(y) : "f"(x)); return y; }
__device__ __forceinline__ float tanh_fast(float x) { float y; asm("tanh.approx.f32 %0, %1;" : "=f"(y) : "f"(x)); return y; }
__device__ __forceinline__ float bf_lo(uint32_t v) { return __uint_as_float(v << 16); }
__device__ __forceinline__ float bf_hi(uint32_t v) { return __uint_as_float(v & 0xFFFF0000u); }
__device__ __forceinline__ uint32_t movm(uint32_t a) {
  uint32_t d;
  asm volatile("movmatrix.sync.aligned.m8n8.trans.b16 %0, %1;" : "=r"(d) : "r"(a));
  return d;
}

__device__ __forceinline__ void wgmma_ss136_tn(float (&d)[68], uint64_t da, uint64_t db, int sd) {
  asm volatile("{\n.reg .pred p;\nsetp.ne.b32 p, %70, 0;\n"
    "wgmma.mma_async.sync.aligned.m64n136k16.f32.bf16.bf16 {%0, %1, %2, %3, %4, %5, %6, %7, %8, %9, %10, %11, %12, %13, %14, %15, %16, %17, %18, %19, %20, %21, %22, %23, %24, %25, %26, %27, %28, %29, %30, %31, %32, %33, %34, %35, %36, %37, %38, %39, %40, %41, %42, %43, %44, %45, %46, %47, %48, %49, %50, %51, %52, %53, %54, %55, %56, %57, %58, %59, %60, %61, %62, %63, %64, %65, %66, %67}, %68, %69, p, 1, 1, 1, 0;\n}\n"
    : "+f"(d[0]), "+f"(d[1]), "+f"(d[2]), "+f"(d[3]), "+f"(d[4]), "+f"(d[5]), "+f"(d[6]), "+f"(d[7]), "+f"(d[8]), "+f"(d[9]), "+f"(d[10]), "+f"(d[11]), "+f"(d[12]), "+f"(d[13]), "+f"(d[14]), "+f"(d[15]), "+f"(d[16]), "+f"(d[17]), "+f"(d[18]), "+f"(d[19]), "+f"(d[20]), "+f"(d[21]), "+f"(d[22]), "+f"(d[23]), "+f"(d[24]), "+f"(d[25]), "+f"(d[26]), "+f"(d[27]), "+f"(d[28]), "+f"(d[29]), "+f"(d[30]), "+f"(d[31]), "+f"(d[32]), "+f"(d[33]), "+f"(d[34]), "+f"(d[35]), "+f"(d[36]), "+f"(d[37]), "+f"(d[38]), "+f"(d[39]), "+f"(d[40]), "+f"(d[41]), "+f"(d[42]), "+f"(d[43]), "+f"(d[44]), "+f"(d[45]), "+f"(d[46]), "+f"(d[47]), "+f"(d[48]), "+f"(d[49]), "+f"(d[50]), "+f"(d[51]), "+f"(d[52]), "+f"(d[53]), "+f"(d[54]), "+f"(d[55]), "+f"(d[56]), "+f"(d[57]), "+f"(d[58]), "+f"(d[59]), "+f"(d[60]), "+f"(d[61]), "+f"(d[62]), "+f"(d[63]), "+f"(d[64]), "+f"(d[65]), "+f"(d[66]), "+f"(d[67])
    : "l"(da), "l"(db), "r"(sd));
}
__device__ __forceinline__ void wgmma_ss128_tt(float (&d)[64], uint64_t da, uint64_t db, int sd) {
  asm volatile("{\n.reg .pred p;\nsetp.ne.b32 p, %66, 0;\n"
    "wgmma.mma_async.sync.aligned.m64n128k16.f32.bf16.bf16 {%0, %1, %2, %3, %4, %5, %6, %7, %8, %9, %10, %11, %12, %13, %14, %15, %16, %17, %18, %19, %20, %21, %22, %23, %24, %25, %26, %27, %28, %29, %30, %31, %32, %33, %34, %35, %36, %37, %38, %39, %40, %41, %42, %43, %44, %45, %46, %47, %48, %49, %50, %51, %52, %53, %54, %55, %56, %57, %58, %59, %60, %61, %62, %63}, %64, %65, p, 1, 1, 1, 1;\n}\n"
    : "+f"(d[0]), "+f"(d[1]), "+f"(d[2]), "+f"(d[3]), "+f"(d[4]), "+f"(d[5]), "+f"(d[6]), "+f"(d[7]), "+f"(d[8]), "+f"(d[9]), "+f"(d[10]), "+f"(d[11]), "+f"(d[12]), "+f"(d[13]), "+f"(d[14]), "+f"(d[15]), "+f"(d[16]), "+f"(d[17]), "+f"(d[18]), "+f"(d[19]), "+f"(d[20]), "+f"(d[21]), "+f"(d[22]), "+f"(d[23]), "+f"(d[24]), "+f"(d[25]), "+f"(d[26]), "+f"(d[27]), "+f"(d[28]), "+f"(d[29]), "+f"(d[30]), "+f"(d[31]), "+f"(d[32]), "+f"(d[33]), "+f"(d[34]), "+f"(d[35]), "+f"(d[36]), "+f"(d[37]), "+f"(d[38]), "+f"(d[39]), "+f"(d[40]), "+f"(d[41]), "+f"(d[42]), "+f"(d[43]), "+f"(d[44]), "+f"(d[45]), "+f"(d[46]), "+f"(d[47]), "+f"(d[48]), "+f"(d[49]), "+f"(d[50]), "+f"(d[51]), "+f"(d[52]), "+f"(d[53]), "+f"(d[54]), "+f"(d[55]), "+f"(d[56]), "+f"(d[57]), "+f"(d[58]), "+f"(d[59]), "+f"(d[60]), "+f"(d[61]), "+f"(d[62]), "+f"(d[63])
    : "l"(da), "l"(db), "r"(sd));
}
__device__ __forceinline__ void wgmma_ss16_tt(float (&d)[8], uint64_t da, uint64_t db, int sd) {
  asm volatile("{\n.reg .pred p;\nsetp.ne.b32 p, %10, 0;\n"
    "wgmma.mma_async.sync.aligned.m64n16k16.f32.bf16.bf16 {%0, %1, %2, %3, %4, %5, %6, %7}, %8, %9, p, 1, 1, 1, 1;\n}\n"
    : "+f"(d[0]), "+f"(d[1]), "+f"(d[2]), "+f"(d[3]), "+f"(d[4]), "+f"(d[5]), "+f"(d[6]), "+f"(d[7])
    : "l"(da), "l"(db), "r"(sd));
}
__device__ __forceinline__ void wgmma_rs64_t_z(float (&d)[32], uint32_t a0, uint32_t a1, uint32_t a2, uint32_t a3, uint64_t db) {
  asm volatile("{\n.reg .pred p;\nsetp.ne.b32 p, 0, 0;\n"
    "wgmma.mma_async.sync.aligned.m64n64k16.f32.bf16.bf16 {%0, %1, %2, %3, %4, %5, %6, %7, %8, %9, %10, %11, %12, %13, %14, %15, %16, %17, %18, %19, %20, %21, %22, %23, %24, %25, %26, %27, %28, %29, %30, %31}, {%32, %33, %34, %35}, %36, p, 1, 1, 1;\n}\n"
    : "=f"(d[0]), "=f"(d[1]), "=f"(d[2]), "=f"(d[3]), "=f"(d[4]), "=f"(d[5]), "=f"(d[6]), "=f"(d[7]), "=f"(d[8]), "=f"(d[9]), "=f"(d[10]), "=f"(d[11]), "=f"(d[12]), "=f"(d[13]), "=f"(d[14]), "=f"(d[15]), "=f"(d[16]), "=f"(d[17]), "=f"(d[18]), "=f"(d[19]), "=f"(d[20]), "=f"(d[21]), "=f"(d[22]), "=f"(d[23]), "=f"(d[24]), "=f"(d[25]), "=f"(d[26]), "=f"(d[27]), "=f"(d[28]), "=f"(d[29]), "=f"(d[30]), "=f"(d[31])
    : "r"(a0), "r"(a1), "r"(a2), "r"(a3), "l"(db));
}
__device__ __forceinline__ void wgmma_rs64_t(float (&d)[32], uint32_t a0, uint32_t a1, uint32_t a2, uint32_t a3, uint64_t db) {
  asm volatile("{\n.reg .pred p;\nsetp.ne.b32 p, 1, 0;\n"
    "wgmma.mma_async.sync.aligned.m64n64k16.f32.bf16.bf16 {%0, %1, %2, %3, %4, %5, %6, %7, %8, %9, %10, %11, %12, %13, %14, %15, %16, %17, %18, %19, %20, %21, %22, %23, %24, %25, %26, %27, %28, %29, %30, %31}, {%32, %33, %34, %35}, %36, p, 1, 1, 1;\n}\n"
    : "+f"(d[0]), "+f"(d[1]), "+f"(d[2]), "+f"(d[3]), "+f"(d[4]), "+f"(d[5]), "+f"(d[6]), "+f"(d[7]), "+f"(d[8]), "+f"(d[9]), "+f"(d[10]), "+f"(d[11]), "+f"(d[12]), "+f"(d[13]), "+f"(d[14]), "+f"(d[15]), "+f"(d[16]), "+f"(d[17]), "+f"(d[18]), "+f"(d[19]), "+f"(d[20]), "+f"(d[21]), "+f"(d[22]), "+f"(d[23]), "+f"(d[24]), "+f"(d[25]), "+f"(d[26]), "+f"(d[27]), "+f"(d[28]), "+f"(d[29]), "+f"(d[30]), "+f"(d[31])
    : "r"(a0), "r"(a1), "r"(a2), "r"(a3), "l"(db));
}
__device__ __forceinline__ void wgmma_rs24_n(float (&d)[12], uint32_t a0, uint32_t a1, uint32_t a2, uint32_t a3, uint64_t db) {
  asm volatile("{\n.reg .pred p;\nsetp.ne.b32 p, 1, 0;\n"
    "wgmma.mma_async.sync.aligned.m64n24k16.f32.bf16.bf16 {%0, %1, %2, %3, %4, %5, %6, %7, %8, %9, %10, %11}, {%12, %13, %14, %15}, %16, p, 1, 1, 0;\n}\n"
    : "+f"(d[0]), "+f"(d[1]), "+f"(d[2]), "+f"(d[3]), "+f"(d[4]), "+f"(d[5]), "+f"(d[6]), "+f"(d[7]), "+f"(d[8]), "+f"(d[9]), "+f"(d[10]), "+f"(d[11])
    : "r"(a0), "r"(a1), "r"(a2), "r"(a3), "l"(db));
}

constexpr uint32_t SB0 = 0x400;
constexpr int NW = 6, WST = 6144, NKV = 4;
constexpr int BST = 12288;
constexpr int SM_RES = 0;
constexpr int SM_KV = 147456;
constexpr int SM_W = SM_KV + NKV * KVB;
constexpr int SM_XR = SM_KV + 4 * WST;
constexpr int SM_B1 = SM_W + NW * WST;
constexpr int SM_ZERO = SM_B1 + 1152;
constexpr int XP = 17408, SM_BIG = 9 * XP;
constexpr int SM_S2 = SM_BIG + 6 * BST;
constexpr int SM_TMP = SM_S2 + 1024;
constexpr int SM_BAR = SM_TMP + 192;
constexpr int SM_TOTAL = SM_BAR + 768;
static_assert(SM_ZERO + 3072 <= SM_S2, "smem");
enum { B_RESE = 0, B_RAW = 9, B_H7 = 18, B_RED,   B_O, B_LN = B_O + 3,   B_RESF, B_WF = B_RESF + 9, B_KVF = B_WF + NW,
       B_ACC = B_KVF + NKV, B_Y, B_OF = B_Y + 9, B_STAT = B_OF + 9, B_XR, B_BIAS, B_TAB, B_QR, B_BIG = B_QR + 4, B_X, B_BF = B_X + 9, B_COUNT = B_BF + 6 };
constexpr int B_H8 = B_RESF + 8;
enum { NB_H6 = 0, NB_WE = 1, NB_KVE = NB_WE + NW, NB_GEMM = NB_KVE + NKV, NB_EPI };
static_assert(NB_EPI + 2 <= 15, "named barriers");
static_assert(B_COUNT * 8 <= 768, "barriers");
static_assert(SM_TOTAL <= 232448, "smem");
struct Descs { uint64_t w, x, h, k0, kx, v; int dbg, sa, sb, sc; };

#define XMASK 0xB5
constexpr uint32_t POLY_MASK = XMASK;
#define RG_A 152
#define RG_G 184
#define RG_P 24
static_assert(2 * RG_A + RG_G + RG_P <= 512, "registers");
constexpr int ZROUND = 0;
#define PFD 2
#define XTHR 0
constexpr uint32_t MAGIC1 = 0x43DF, MAGIC2 = 0xBF15, MAGIC3 = 0xB9AF;

__device__ __forceinline__ int qkv_chunk(int p) { return (p % 3) * 9 + p / 3; }

__device__ __forceinline__ float gelu_half(float w) {
  float p = fmaf(w * w, 8.0f * 0.044715f * 0.7978845608028654f, 2.0f * 0.7978845608028654f);
  float t = tanh_fast(w * p);
  return fmaf(w, t, w);
}

struct GState { bool lead; uint32_t ready; };

template <bool GELU, bool DRAINED, bool RES, class F>
__device__ __forceinline__ void gemm_chunk(float (&cur)[64], float (&prev)[64], uint8_t* gp, GState& st, const Descs& ds,
                                           int sig, bool do_epi, bool accum, uint32_t nores, uint32_t resbar, int target, F&& hook) {
  constexpr uint32_t bar = SB0 + SM_BAR;
  int prog;
  const uint64_t z = (uint64_t)(uint32_t)(sig >> 8);
  const uint64_t da = ds.w + z, da2 = ds.w + (uint64_t)(uint32_t)(sig >> 9), db = ds.h + z;
#pragma unroll
  for (int j = 0; j < 12; j++) {
    if (j == 8) hook();
    if (RES) {
      const int b0 = (j == 0) ? 0 : (3 * j - 1) / 4 + 1, b1 = (3 * j + 2) / 4;
#pragma unroll
      for (int b = b0; b <= b1; b++) mbar_wait_unless(nores, resbar + b * 8, 0);
    }
    mbar_wait_unless(st.ready, bar + (B_WF + j % NW) * 8, (j / NW) & 1);
    if (j % 4 == 0) asm volatile("ld.volatile.shared.s32 %0, [%1];" : "=r"(prog) : "r"(SB0 + SM_TMP + 32));
    wg_fence();
#pragma unroll
    for (int u = 0; u < 3; u++) {
      const int ks = 3 * j + u;
      wgmma_ss128_tt(cur, (j < NW ? da : da2) + ((SM_W + (NW - 1 - j % NW) * WST) / 16 + u * 128), db + ks * 256, ks != 0 || accum);
    }
    wg_commit();
    st.ready = mbar_test(bar + (B_WF + (j + 1) % NW) * 8, ((j + 1) / NW) & 1);
    const int e = DRAINED ? j : j - 1;
    if (GELU) {
      if (e < 10) {
#pragma unroll
        for (int i = (32 * e) / 10; i < (32 * (e + 1)) / 10; i++)
          st32(gp + (i >> 1) * 128 + (i & 1) * 2048, pack_bf16(gelu_half(prev[2 * i]), gelu_half(prev[2 * i + 1])));
      }
    } else if (e >= 0 && e < (DRAINED ? 8 : 7)) {
#pragma unroll
      for (int i = (16 * e) / (DRAINED ? 8 : 7); i < (16 * (e + 1)) / (DRAINED ? 8 : 7); i++)
        asm volatile("{\n.reg .pred p;\nsetp.ne.u32 p, %5, 0;\n@p red.global.add.v4.f32 [%0], {%1,%2,%3,%4};\n}" ::"l"(gp + i * 512), "f"(prev[4 * i]),
                     "f"(prev[4 * i + 1]), "f"(prev[4 * i + 2]), "f"(prev[4 * i + 3]), "r"((uint32_t)do_epi) : "memory");
    }
    if (!DRAINED || j > 0) {
      wg_wait<1>();
      if (j > 0 || do_epi) nb_arrive(NB_WE + (j + NW - 1) % NW, 160);
    }
    if (j < 11) asm volatile("{\n.reg .pred p;\nsetp.lt.s32 p, %0, %1;\n@p wgmma.wait_group.sync.aligned 0;\n}" ::"r"(prog), "r"(target + j / 4) : "memory");
    if (!DRAINED && j == 0) pin(prev);
    if (GELU && e == 9) {
      if (sig == 7) nb_arrive(NB_H6, 160);
      if (sig >= 8) {
        asm volatile("fence.proxy.async.shared::cta;" ::: "memory");
        __syncwarp();
        if (st.lead) mbar_arrive(bar + (sig == 8 ? B_H7 : B_H8) * 8);
      }
    }
    if (!GELU && RES && e == 6 && sig == 8) { __syncwarp(); if (st.lead) mbar_arrive(bar + B_RED * 8); }
    if (RES) {
      if (j > 0 && (3 * j) / 4 > (3 * (j - 1)) / 4 && sig == 8 && st.lead) mbar_arrive(bar + (B_RESE + (3 * j) / 4 - 1) * 8);
    }
  }
}
__device__ __forceinline__ void gemm_drain(float (&cur)[64]) {
  wg_wait<0>();
  pin(cur);
  nb_arrive(NB_WE + NW - 1, 160);
}

__device__ __forceinline__ uint32_t exp2_pair_fix(float t0, float t1, uint32_t kc) {
  uint32_t z = __byte_perm(__float_as_uint(t0), __float_as_uint(t1), 0x6521);
  uint32_t mh;
  asm("lop3.b32 %0, %1, 0x007F007F, %2, 0xEA;" : "=r"(mh) : "r"(z), "r"(kc));
  uint32_t e = z - mh;
  uint32_t r;
  asm("fma.rn.bf16x2 %0, %1, %2, %3;" : "=r"(r) : "r"(z), "r"(mh), "r"(e));
  return r;
}
__device__ __forceinline__ void softmax_tile(const float (&s)[32], uint32_t (&p)[16], uint32_t kc) {
#pragma unroll
  for (int i = 0; i < 8; i++) {
    if ((POLY_MASK >> i) & 1) {
      p[2 * i + 0] = exp2_pair_fix(s[4 * i + 0], s[4 * i + 1], kc);
      p[2 * i + 1] = exp2_pair_fix(s[4 * i + 2], s[4 * i + 3], kc);
    } else {
      p[2 * i + 0] = pack_bf16(ex2f(s[4 * i + 0]), ex2f(s[4 * i + 1]));
      p[2 * i + 1] = pack_bf16(ex2f(s[4 * i + 2]), ex2f(s[4 * i + 3]));
    }
  }
}

__device__ __forceinline__ float max_sqnorm(uint32_t a0, uint32_t a1, uint32_t a2, uint32_t b0, uint32_t b1, uint32_t b2) {
  auto H = [](uint32_t v) { return *reinterpret_cast<__nv_bfloat162*>(&v); };
  __nv_bfloat162 sa = __hfma2(H(a0), H(a0), __hfma2(H(a1), H(a1), __hmul2(H(a2), H(a2))));
  __nv_bfloat162 sb = __hfma2(H(b0), H(b0), __hfma2(H(b1), H(b1), __hmul2(H(b2), H(b2))));
#pragma unroll
  for (int o = 4; o <= 16; o <<= 1) { sa = __hadd2(sa, __shfl_xor_sync(~0u, sa, o)); sb = __hadd2(sb, __shfl_xor_sync(~0u, sb, o)); }
  sa = __hmax2_nan(sa, sb);
#pragma unroll
  for (int o = 1; o <= 2; o <<= 1) sa = __hmax2_nan(sa, __shfl_xor_sync(~0u, sa, o));
  return __bfloat162float(__hmax_nan(sa.x, sa.y));
}
__device__ __forceinline__ void mma16816(float* d, uint32_t a0, uint32_t a1, uint32_t a2, uint32_t a3, uint32_t b0, uint32_t b1) {
  asm volatile("mma.sync.aligned.m16n8k16.row.col.f32.bf16.bf16.f32 {%0,%1,%2,%3}, {%4,%5,%6,%7}, {%8,%9}, {%0,%1,%2,%3};"
               : "+f"(d[0]), "+f"(d[1]), "+f"(d[2]), "+f"(d[3]) : "r"(a0), "r"(a1), "r"(a2), "r"(a3), "r"(b0), "r"(b1));
}
__device__ __forceinline__ void attn_safe(float (&o)[12], const uint8_t* kv, uint32_t q0, uint32_t q1, uint32_t q2, uint32_t q3, uint32_t q4, uint32_t q5) {
  float m0 = -INFINITY, m1 = -INFINITY;
#pragma unroll
  for (int i = 0; i < 12; i++) o[i] = 0.f;
#pragma unroll 1
  for (int kt = 0; kt < S_ / 16; kt++) {
    const uint8_t* p = kv + (size_t)(kt >> 3) * KVB + (kt & 7) * 256;
    uint32_t f[5][2];
#pragma unroll
    for (int pl = 0; pl < 5; pl++) { f[pl][0] = __ldcg((const uint32_t*)(p + pl * 2048)); f[pl][1] = __ldcg((const uint32_t*)(p + pl * 2048 + 128)); }
    float s[2][4];
#pragma unroll
    for (int n = 0; n < 2; n++) {
      s[n][0] = s[n][1] = s[n][2] = s[n][3] = 0.f;
      mma16816(s[n], q0, q1, q2, q3, movm(f[0][n]), movm(f[1][n]));
      mma16816(s[n], q4, q5, 0u, 0u, movm(f[4][n]), 0u);
    }
    float n0 = fmaxf(fmaxf(s[0][0], s[0][1]), fmaxf(s[1][0], s[1][1])), n1 = fmaxf(fmaxf(s[0][2], s[0][3]), fmaxf(s[1][2], s[1][3]));
#pragma unroll
    for (int d = 1; d <= 2; d <<= 1) { n0 = fmaxf(n0, __shfl_xor_sync(~0u, n0, d)); n1 = fmaxf(n1, __shfl_xor_sync(~0u, n1, d)); }
    n0 = fmaxf(n0, m0); n1 = fmaxf(n1, m1);
    const float c0 = ex2f(m0 - n0), c1 = ex2f(m1 - n1);
    m0 = n0; m1 = n1;
#pragma unroll
    for (int i = 0; i < 12; i++) o[i] *= (i & 2) ? c1 : c0;
    const uint32_t p0 = pack_bf16(ex2f(s[0][0] - m0), ex2f(s[0][1] - m0)), p1 = pack_bf16(ex2f(s[0][2] - m1), ex2f(s[0][3] - m1));
    const uint32_t p2 = pack_bf16(ex2f(s[1][0] - m0), ex2f(s[1][1] - m0)), p3 = pack_bf16(ex2f(s[1][2] - m1), ex2f(s[1][3] - m1));
#pragma unroll
    for (int n = 0; n < 3; n++) mma16816(o + 4 * n, p0, p1, p2, p3, f[2 + n][0], f[2 + n][1]);
  }
}

#define TMA2D(...) tma2d_h(__VA_ARGS__, pol)
#define BULKLD(...) bulk_ld_h(__VA_ARGS__, pol)
__global__ void __launch_bounds__(512, 1)
main_kernel(const __grid_constant__ CUtensorMap tm_x, const __grid_constant__ CUtensorMap tm_wqkv,
            const __grid_constant__ CUtensorMap tm_w1, const __grid_constant__ CUtensorMap tm_w2,
            const __grid_constant__ CUtensorMap tm_wo, const __grid_constant__ CUtensorMap tm_out,
            const __grid_constant__ Descs ds, const bf16* __restrict__ x, const bf16* __restrict__ b1,
            const bf16* __restrict__ b2, bf16* __restrict__ out, const uint8_t* __restrict__ wqkv,
            const uint8_t* __restrict__ w1, const uint8_t* __restrict__ w2, const uint8_t* __restrict__ wo) {
  extern __shared__ __align__(1024) uint8_t smem[];
  if (smem_u32(smem) != SB0) __trap();
  constexpr uint32_t sb = SB0;
  constexpr uint32_t bar = sb + SM_BAR;
#define ROT 0
  const int tid = (ROT == 0) ? threadIdx.x : (ROT == 1) ? ((threadIdx.x + 256) & 511) : (ROT == 2) ? (511 - 127 - (threadIdx.x & ~127) + (threadIdx.x & 127)) :
                  ((threadIdx.x < 128) ? threadIdx.x + 256 : (threadIdx.x < 384 ? threadIdx.x - 128 : threadIdx.x));
  const int lane = tid & 31;
  const int warp = __shfl_sync(0xffffffffu, tid >> 5, 0);
  const bool spare = blockIdx.x >= NRT * NG;
  const int r = spare ? (blockIdx.x - NRT * NG) * 4 : blockIdx.x >> 3, g = blockIdx.x & 7;
  const int nq = spare ? 12 : 3;
  auto job_chunk = [&](int ch) { return qkv_chunk(spare ? 24 + ch % 3 : g + 8 * ch); };
  TSC(tid == 0, 0);

  uint32_t xv[2][9], xt[18];
  if (warp < 8 && !spare) {
    const uint32_t* xr = (const uint32_t*)(x + (size_t)(r * 128 + g * 16 + warp * 2) * D_);
#pragma unroll
    for (int j = 0; j < 18; j++) xv[j / 9][j % 9] = __ldg(xr + j * 32 + lane);
    const uint32_t* xp = (const uint32_t*)(x + (size_t)(r * 128 + (2 * g + (warp & 1)) * 8 + (lane >> 2)) * D_ + (warp >> 1) * 16) + (lane & 3);
#pragma unroll
    for (int c = 0; c < 18; c++) xt[c] = __ldg(xp + (c >> 1) * 32 + (c & 1) * 4);
  }
  if (warp == 13 || warp == 12) {
    const bool el0 = elect_one();
    if (el0) {
      if (warp == 13) {
#pragma unroll
        for (int kb = 0; kb < 9; kb++) mbar_init(bar + (B_X + kb) * 8, 1);
      } else {
#pragma unroll
        for (int s = 0; s < 6; s++) mbar_init(bar + (B_BF + s) * 8, 1);
      }
      asm volatile("fence.mbarrier_init.release.cluster;" ::: "memory");
    }
    __syncwarp();
    nb_arrive(0, 512);
    if (el0) {
      if (warp == 13) {
#pragma unroll
        for (int kb = 0; kb < 9; kb++) {
          mbar_expect(bar + (B_X + kb) * 8, 16384);
          tma2d(sb + kb * XP, &tm_x, kb * 64, r * 128, bar + (B_X + kb) * 8);
        }
      } else {
        const int c0 = job_chunk(0) * 64;
#pragma unroll
        for (int s = 0; s < 6; s++) {
          mbar_expect(bar + (B_BF + s) * 8, BST);
          tma2d(sb + SM_BIG + (5 - s) * BST, &tm_wqkv, c0, s * 96, bar + (B_BF + s) * 8);
        }
      }
    }
    __syncwarp();
    nb_sync(15, 512);
  } else {
    if (warp < 12) {
      if (elect_one()) {
#pragma unroll
        for (int k = 0; k < (B_X + 11) / 12; k++) {
          const int i = warp + 12 * k;
          if (i < B_X) mbar_init(bar + i * 8, (i < B_O || i == B_H8 || i == B_OF + 7 || i == B_OF + 8) ? 4 : (i < B_RESF ? 8 : (i == B_OF + 6 ? 5 : (i == B_TAB ? 12 : 1))));
        }
        asm volatile("fence.mbarrier_init.release.cluster;" ::: "memory");
      }
    } else {
      if (tid == 448) sts32(sb + SM_TMP + 32, 1000);
#pragma unroll
      for (int kb = 0; kb < 9; kb++) *(uint4*)(smem + kb * XP + 16384 + (tid - 448) * 16) = make_uint4(0x3F803F80u, 0x3F803F80u, 0x3F803F80u, 0x3F803F80u);
      asm volatile("fence.proxy.async.shared::cta;" ::: "memory");
    }
    __syncwarp();
    nb_arrive(15, 512);
    nb_sync(0, 512);
    if (warp < 8 && !spare) {
      float mu[2], sq[2];
#pragma unroll
      for (int k = 0; k < 2; k++) {
        mu[k] = 0.f;
#pragma unroll
        for (int j = 0; j < 9; j++) mu[k] += bf_lo(xv[k][j]) + bf_hi(xv[k][j]);
      }
#pragma unroll
      for (int o = 16; o; o >>= 1) { mu[0] += __shfl_xor_sync(~0u, mu[0], o); mu[1] += __shfl_xor_sync(~0u, mu[1], o); }
#pragma unroll
      for (int k = 0; k < 2; k++) {
        mu[k] *= (1.0f / D_);
        sq[k] = 0.f;
#pragma unroll
        for (int j = 0; j < 9; j++) { float a = bf_lo(xv[k][j]) - mu[k], b = bf_hi(xv[k][j]) - mu[k]; sq[k] = fmaf(a, a, fmaf(b, b, sq[k])); }
      }
#pragma unroll
      for (int o = 16; o; o >>= 1) { sq[0] += __shfl_xor_sync(~0u, sq[0], o); sq[1] += __shfl_xor_sync(~0u, sq[1], o); }
#pragma unroll
      for (int k = 0; k < 2; k++) {
        const float var = sq[k] * (1.0f / D_);
        const float rs1 = rsqrtf(var + 1e-5f);
        const float sc = rs1 * rsqrtf(fmaf(var * rs1, rs1, 1e-5f));
        if (lane == 0) {
          asm volatile("st.relaxed.gpu.global.v2.f32 [%0], {%1,%2};" ::"l"(g_st + r * 128 + g * 16 + warp * 2 + k), "f"(mu[k]), "f"(rs1) : "memory");
          *(float2*)(smem + SM_TMP + 64 + (warp * 2 + k) * 8) = make_float2(sc, -mu[k] * sc);
        }
      }
      nb_sync(NB_KVE, 256);
    {
      const float4 sn = *(const float4*)(smem + SM_TMP + 64 + ((warp & 1) * 8 + 2 * (lane & 3)) * 8);
      uint8_t* yp = g_y + (size_t)r * 147456 + (warp >> 1) * 4096 + (2 * g + (warp & 1)) * 128 + lane * 4;
#pragma unroll
      for (int c = 0; c < 18; c++) {
        const uint32_t v = movm(xt[c]);
        stg32(yp + (c >> 1) * 16384 + (c & 1) * 2048, pack_bf16(fmaf(bf_lo(v), sn.x, sn.y), fmaf(bf_hi(v), sn.z, sn.w)));
      }
      uint4* sp = (uint4*)(g_o + (size_t)r * 147456 + 54 * 2048 + g * 4608) + tid;
      sp[0] = make_uint4(~0u, ~0u, ~0u, ~0u);
      if (tid < 32) sp[256] = make_uint4(~0u, ~0u, ~0u, ~0u);
      __syncwarp();
      if (lane == 0) mbar_arrive(bar + B_LN * 8);
      TSC(tid == 32, 3);
    }
    }
  }

  if (warp < 12) {
    const int c3 = (warp >> 2) == 2 ? 0 : (warp >> 2) + 1;
    const int w = warp & 3, gq = lane >> 2, t = lane & 3;
    float qa[68];
#pragma unroll
    for (int i = 0; i < 68; i++) asm volatile("" : "=f"(qa[i]));
#pragma unroll 1
    for (int ch = c3; ch < nq; ch += 3) {
      const int tl = ch / 3;
      const uint64_t z = (uint64_t)(uint32_t)(ch >> 8);
      const uint64_t da = ds.w + z, db = ds.x + z;
      if (ch > 0) nb_sync(NB_KVE + 1 + c3, 256);
#pragma unroll
      for (int j = 0; j < 6; j++) {
        const int b0 = (j == 0) ? 0 : (6 * j - 1) / 4 + 1, b1 = (6 * j + 5) / 4;
#pragma unroll
        for (int b = b0; b <= b1; b++) mbar_wait_unless((uint32_t)c3, bar + (B_X + b) * 8, tl & 1);
        mbar_wait(bar + (B_BF + j) * 8, ch & 1);
        wg_fence();
#pragma unroll
        for (int u = 0; u < 6; u++) {
          const int ks = 6 * j + u;
          wgmma_ss136_tn(qa, da + ((SM_BIG + (5 - j) * BST) / 16 + u * 128), db + ((ks >> 2) * (XP / 16) + (ks & 3) * 2), ks != 0);
        }
        wg_commit();
        if (j == 5 && ch + 1 < nq) nb_arrive(NB_KVE + 1 + (c3 == 2 ? 0 : c3 + 1), 256);
        if (j > 0) {
          wg_wait<1>();
          nb_arrive(NB_WE + j - 1, 160);
          if (c3 == 2 && lane == 0) {
#pragma unroll
            for (int b = (6 * (j - 1)) / 4; b < (6 * j) / 4; b++) mbar_arrive(bar + (B_RAW + b) * 8);
          }
        }
      }
      const int cq = job_chunk(ch);
      const int part = cq / 9;
      uint8_t* pp[2];
#pragma unroll
      for (int hf = 0; hf < 2; hf++) {
        const int jj = (cq - part * 9) * 64 + w * 16 + hf * 8 + gq;
        const int head = jj / 18, dim = jj - head * 18;
        const int pl = (part == 0) ? 0 : (part - 1) * 2;
        const int off = (dim < 16) ? (pl + (dim >> 3)) * 2048 + (dim & 7) * 16 : (part == 0 ? 2 : 4) * 2048 + (pl + dim - 16) * 16;
        pp[hf] = (part == 0 ? g_q : g_kv) + (size_t)(head * NRT + r + tl) * (part == 0 ? QB : KVB) + off + t * 4;
      }
      const float qs = (part == 0) ? (0.23570226039551584f * 1.4426950408889634f) : 1.0f;
      mbar_wait(bar + B_STAT * 8, tl & 1);
      float4 sv[8];
#pragma unroll
      for (int i = 0; i < 8; i++) { sv[i] = *(const float4*)(smem + SM_S2 + t * 16 + i * 64); sv[i].y *= qs; sv[i].w *= qs; }
      wg_wait<0>();
      pin(qa);
      nb_arrive(NB_WE + 5, 160);
      if (c3 == 2 && lane == 0) { mbar_arrive(bar + (B_RAW + 7) * 8); mbar_arrive(bar + (B_RAW + 8) * 8); }
      TSC((tid & 127) == 0 && ch < 3, 8 + ch);
      const float c0 = -qa[64], c1 = -qa[66];
#pragma unroll
      for (int hh = 0; hh < 2; hh++) {
        if (hh) {
#pragma unroll
          for (int i = 0; i < 8; i++) { sv[i] = *(const float4*)(smem + SM_S2 + t * 16 + (8 + i) * 64); sv[i].y *= qs; sv[i].w *= qs; }
        }
#pragma unroll
        for (int k = 0; k < 8; k++) {
          const int i = hh * 8 + k;
          stg32(pp[0] + i * 128, pack_bf16(fmaf(sv[k].x, c0, qa[4 * i]) * sv[k].y, fmaf(sv[k].z, c0, qa[4 * i + 1]) * sv[k].w));
          stg32(pp[1] + i * 128, pack_bf16(fmaf(sv[k].x, c1, qa[4 * i + 2]) * sv[k].y, fmaf(sv[k].z, c1, qa[4 * i + 3]) * sv[k].w));
        }
      }
      if (spare) { nb_sync(NB_EPI + c3, 160); if (lane == 0) mbar_arrive(bar + B_TAB * 8); }
      else nb_arrive(NB_EPI + c3, 160);
    }
  }

  if (warp >= 12) {
    asm volatile("setmaxnreg.dec.sync.aligned.u32 %0;" ::"n"(RG_P));
    const bool el = elect_one();
    const uint64_t pol = policy_evict_first();
    auto finish = [&]() {
      if (atomicAdd(&g_flags.done.v, 1u) == NRT * NG - 1) {
        Flag* f = (Flag*)&g_flags;
        for (int i = 0; i < (int)(sizeof(Flags) / sizeof(Flag)); i++) f[i].v = 0u;
        g_epoch = *(volatile unsigned*)&g_epoch + 1u;
      }
    };
    if (warp == 12) {
#pragma unroll 1
      for (int ch = 1; ch < nq; ch++) {
        const int c0 = job_chunk(ch) * 64;
#pragma unroll
        for (int s = 0; s < 6; s++) {
          nb_sync(NB_WE + s, 160);
          if (el) {
            mbar_expect(bar + (B_BF + s) * 8, BST);
            TMA2D(sb + SM_BIG + (5 - s) * BST, &tm_wqkv, c0, s * 96, bar + (B_BF + s) * 8);
          }
        }
      }
      if (!spare) {
#pragma unroll
        for (int s = 0; s < 6; s++) {
          nb_sync(NB_WE + s, 160);
          if (el) {
#pragma unroll
            for (int k = 0; k < NW; k++)
              if ((k + 1) / 2 == s) {
                mbar_expect(bar + (B_WF + k) * 8, WST);
                TMA2D(sb + SM_W + (NW - 1 - k) * WST, &tm_w1, g * 576, k * 48, bar + (B_WF + k) * 8);
              }
          }
        }
        if (el) {
          mbar_arrive(bar + B_BIG * 8);
          mbar_expect(bar + B_BIAS * 8, 1152);
          bulk_ld(sb + SM_B1, b1 + g * 576, 1152, bar + B_BIAS * 8);
        }
        auto half = [&](const CUtensorMap* tm, int c0, int k0) {
#pragma unroll
          for (int s = 0; s < NW; s++) {
            nb_sync(NB_WE + s, 160);
            if (el) {
              mbar_expect(bar + (B_WF + s) * 8, WST);
              TMA2D(sb + SM_W + (NW - 1 - s) * WST, tm, c0, k0 + s * 48, bar + (B_WF + s) * 8);
            }
          }
        };
        auto pf = [&](const CUtensorMap* tm, int c0, int k0) {
          if (r < 12 && el) asm volatile("cp.async.bulk.prefetch.tensor.2d.L2.global [%0, {%1, %2}];" ::"l"(tm), "r"(c0), "r"(k0 + r * 48) : "memory");
        };
        int c = (g + 1) * 64, cp = c;
        half(&tm_w1, g * 576, 288);
#pragma unroll 1
        for (int ch = 1; ch < 9; ch++) {
          if (ch < 7) pf(&tm_w1, g * 576 + (ch + 2) * 64, 0);
          else { pf(&tm_w2, cp, g * 576); cp += 64; if (cp == 576) cp = 0; }
          half(&tm_w1, g * 576 + ch * 64, 0);
          half(&tm_w1, g * 576 + ch * 64, 288);
        }
#pragma unroll 1
        for (int ch = 0; ch < 9; ch++) {
          if (ch < 7) { pf(&tm_w2, cp, g * 576); cp += 64; if (cp == 576) cp = 0; }
          half(&tm_w2, c, g * 576);
          half(&tm_w2, c, g * 576 + 288);
          c += 64; if (c == 576) c = 0;
        }
#pragma unroll 1
        for (int hc = 0; hc < 2; hc++) half(&tm_wo, g * 64, hc * 288);
      }
#pragma unroll
      for (int s = 0; s < NW; s++) nb_sync(NB_WE + s, 160);
    } else if (warp == 13) {
      if (spare) {
        if (el)
          for (int tl = 1; tl < 4; tl++)
            for (int kb = 0; kb < 9; kb++) {
              mbar_wait_slow(bar + (B_RAW + kb) * 8, (tl - 1) & 1);
              mbar_expect(bar + (B_X + kb) * 8, 16384);
              TMA2D(sb + kb * XP, &tm_x, kb * 64, (r + tl) * 128, bar + (B_X + kb) * 8);
            }
      } else {
        const unsigned tag = *(volatile unsigned*)&g_epoch + 1u;
        for (int j = 0; j < 4; j++) {
          const int h = g + 8 * j;
          const int c_lo = (h * 18) >> 6, c_hi = (h * 18 + 17) >> 6;
          if (lane < 7) flag_wait(&g_flags.qkv[lane == 6 ? 27 + g / 2 : (lane >> 1) * 9 + ((lane & 1) ? c_hi : c_lo)], lane == 6 ? 2 * NRT : NRT);
          __syncwarp();
          if (el) { mbar_arrive(bar + (B_QR + j) * 8); asm volatile("fence.proxy.async.global;" ::: "memory"); }
          if (j == 0) mbar_wait_slow(bar + B_BIG * 8, 0);
          const uint8_t* src = g_kv + (size_t)h * NRT * KVB;
#pragma unroll 1
          for (int t4 = 0; t4 < NRT / NKV; t4++) {
            if (t4 == 3) {
              uint4 v0, v1;
              int it = 0;
              do {
                asm volatile("ld.relaxed.gpu.global.v2.u32 {%0,%1}, [%2];" : "=r"(v0.x), "=r"(v0.y) : "l"(g_kn + h * 128 + lane) : "memory");
                asm volatile("ld.relaxed.gpu.global.v2.u32 {%0,%1}, [%2];" : "=r"(v0.z), "=r"(v0.w) : "l"(g_kn + h * 128 + 32 + lane) : "memory");
                asm volatile("ld.relaxed.gpu.global.v2.u32 {%0,%1}, [%2];" : "=r"(v1.x), "=r"(v1.y) : "l"(g_kn + h * 128 + 64 + lane) : "memory");
                asm volatile("ld.relaxed.gpu.global.v2.u32 {%0,%1}, [%2];" : "=r"(v1.z), "=r"(v1.w) : "l"(g_kn + h * 128 + 96 + lane) : "memory");
                if (++it > 4000000) __trap();
              } while (!__all_sync(~0u, v0.y == tag && v0.w == tag && v1.y == tag && v1.w == tag));
              const unsigned mx = __reduce_max_sync(~0u, max(max(v0.x, v0.z), max(v1.x, v1.z)));
              if (el) sts32(sb + SM_TMP + j * 4, mx);
            }
#pragma unroll
            for (int s = 0; s < NKV; s++) {
              if (j > 0 || t4 > 0) nb_sync(NB_KVE + s, 288);
              if (el) {
                mbar_expect(bar + (B_KVF + s) * 8, KVB);
                BULKLD(sb + SM_KV + s * KVB, src + s * KVB, KVB, bar + (B_KVF + s) * 8);
                sts32(sb + SM_TMP + 32, j * 16 + t4 * 4 + s);
                TSC(j == 0 && t4 == 0 && s == 0, 49);
              }
            }
            src += NKV * KVB;
          }
        }
        for (int s = 0; s < NKV; s++) { nb_sync(NB_KVE + s, 288); if (el) sts32(sb + SM_TMP + 32, s < 2 ? 64 + s : 1000); }
        if (el) {
          mbar_expect(bar + B_XR * 8, 16384);
          TMA2D(sb + SM_XR, &tm_x, g * 64, r * 128, bar + B_XR * 8);
        }
#pragma unroll 1
        for (int t = 0; t < 12; t++) {
          const int s = t & (NKV - 1);
          if (t >= NKV) nb_sync(NB_KVE + s, 160);
          if (el) {
            mbar_expect(bar + (B_KVF + s) * 8, WST);
            TMA2D(sb + SM_KV + s * WST, &tm_wo, 512, t * 48, bar + (B_KVF + s) * 8);
          }
        }
      }
    } else if (warp == 14) {
      for (int tl = 0; tl < (spare ? 4 : 1); tl++) {
        float2 sv[4];
        int it = 0;
        bool ok;
        do {
          ok = true;
#pragma unroll
          for (int i = 0; i < 4; i++) {
            asm volatile("ld.relaxed.gpu.global.v2.f32 {%0,%1}, [%2];" : "=f"(sv[i].x), "=f"(sv[i].y) : "l"(g_st + (r + tl) * 128 + i * 32 + lane) : "memory");
            ok = ok && (sv[i].y != 0.f);
          }
          if (++it > 2000000) __trap();
        } while (!__all_sync(~0u, ok));
        if (tl > 0) mbar_wait_slow(bar + B_TAB * 8, (tl - 1) & 1);
#pragma unroll
        for (int i = 0; i < 4; i++) *(float2*)(smem + SM_S2 + (i * 32 + lane) * 8) = sv[i];
        __syncwarp();
        if (el) { mbar_arrive(bar + B_STAT * 8); TSC(1, 2); }
      }
      if (!spare) {
        if (el) {
          mbar_wait_slow(bar + B_LN * 8, 0);
          flag_add(&g_flags.ln[r]);
          if (r < 12)
            for (int c = 0; c < 3; c++)
              asm volatile("cp.async.bulk.prefetch.tensor.2d.L2.global [%0, {%1, %2}];" ::"l"(&tm_w1), "r"(g * 576 + c * 64), "r"(r * 48) : "memory");
          TSC(1, 44);
          flag_wait(&g_flags.ln[r], NG);
          fence_async_all();
          TSC(1, 45);
          for (int kb = 0; kb < 9; kb++) {
            mbar_wait_slow(bar + (B_RAW + kb) * 8, 0);
            mbar_expect(bar + (B_Y + kb) * 8, 16384);
            BULKLD(sb + SM_RES + kb * 16384, g_y + (size_t)r * 147456 + kb * 16384, 16384, bar + (B_Y + kb) * 8);
          }

        }
        __syncwarp();
        nb_sync(NB_H6, 160);
        if (el) {
          flag_wait(&g_flags.ocnt[r * 4 + ZROUND], NG);
          const uint8_t* src = g_h + (size_t)(r * 72 + g * 9) * 16384;
          asm volatile("fence.acq_rel.gpu;" ::: "memory"); fence_async_all();
          for (int kb = 0; kb < 8; kb++) {
            mbar_wait_slow(bar + (B_RESE + kb) * 8, 0);
            if (kb == 7) { mbar_wait_slow(bar + B_H7 * 8, 0); asm volatile("fence.acq_rel.gpu;" ::: "memory"); fence_async_all(); }
            mbar_expect(bar + (B_RESF + kb) * 8, 16384);
            BULKLD(sb + SM_RES + kb * 16384, src + (size_t)kb * 16384, 16384, bar + (B_RESF + kb) * 8);
          }
          flag_wait_sleep(&g_flags.ocnt[r * 4 + 1], NG);
          flag_wait_sleep(&g_flags.ocnt[r * 4 + 2], NG);
          fence_async_all();
          l2_prefetch(x + (size_t)(r * 128 + g * 16) * D_, 16 * D_ * 2);
          l2_prefetch(wo + blockIdx.x * 5184, 5184);
          mbar_wait_sleep(bar + B_RESE * 8, 1);
          for (int kb = 0; kb < 7; kb++) {
            const uint32_t bytes = kb < 6 ? 16384 : 12288;
            mbar_wait_slow(bar + (B_RESE + kb) * 8, 1);
            mbar_expect(bar + (B_OF + kb) * 8, bytes);
            BULKLD(sb + SM_RES + kb * 16384, g_o + (size_t)r * 147456 + kb * 16384, bytes, bar + (B_OF + kb) * 8);
          }
          mbar_wait_slow(bar + (B_OF + 8) * 8, 0);
          mbar_wait_slow(bar + B_ACC * 8, 0);
          for (int i = 0; i < 8; i++) *(float4*)(g_st + r * 128 + g * 16 + i * 2) = make_float4(0.f, 0.f, 0.f, 0.f);
          finish();
        }
      }
    } else {
      if (!spare) {
        if (el && r < 12)
          asm volatile("cp.async.bulk.prefetch.tensor.2d.L2.global [%0, {%1, %2}];" ::"l"(&tm_wqkv), "r"(job_chunk(1 + r / 6) * 64), "r"((r % 6) * 96) : "memory");
#pragma unroll 1
        for (int i = lane; i < 256; i += 32) {
          const int j = i >> 6, grp = (i >> 2) & 15, rw = i & 3;
          const bool poly = (POLY_MASK >> (grp & 7)) & 1;
          uint32_t v = (rw == 1) ? 0x3F80u : (!poly ? 0u : (rw == 0 ? MAGIC1 : (rw == 2 ? MAGIC2 : MAGIC3)));
          v |= v << 16;
          *(uint4*)(g_kv + (size_t)((g + 8 * j) * NRT + r) * KVB + 4 * 2048 + grp * 128 + 64 + rw * 16) = make_uint4(v, v, v, v);
        }
        __syncwarp();
        if (el) flag_add(&g_flags.qkv[27 + g / 2]);
      }
      for (int ch = 0; ch < nq; ch++) {
        __syncwarp();
        nb_sync(NB_EPI + ch % 3, 160);
        if (el) flag_add(&g_flags.qkv[job_chunk(ch)]);
        TSC(el && ch < 2, 52 + ch);
      }
      if (!spare) {
        __syncwarp();
#pragma unroll
        for (int i = 0; i < 6; i++) *(uint4*)(smem + SM_ZERO + (i * 32 + lane) * 16) = make_uint4(0u, 0u, 0u, 0u);
        asm volatile("fence.proxy.async.shared::cta;" ::: "memory");
        __syncwarp();
      }
      if (el && !spare) {
        for (int j = 0; j < 3; j++) {
          mbar_wait_sleep(bar + (B_O + j) * 8, 0);
          if (j == ZROUND) {
            uint8_t* zp = (uint8_t*)(g_acc + (size_t)r * 9 * 8192 + g * 9216);
#pragma unroll 1
            for (int i = 0; i < 12; i++) {
              asm volatile("cp.async.bulk.global.shared::cta.bulk_group [%0], [%1], 3072;" ::"l"(zp + i * 3072), "r"(sb + SM_ZERO) : "memory");
              __nanosleep(400);
            }
            asm volatile("cp.async.bulk.commit_group;\ncp.async.bulk.wait_group 0;" ::: "memory");
            fence_async_all();
          }
          flag_add(&g_flags.ocnt[r * 4 + j]);
        }
        mbar_wait_slow(bar + B_RED * 8, 0);
        flag_add(&g_flags.red[r]);
        flag_wait(&g_flags.red[r], NG);
        mbar_arrive(bar + B_ACC * 8);
        TSC(1, 41);
      }
    }
  } else if (spare) {
  } else if (warp >= 8) {
    asm volatile("setmaxnreg.inc.sync.aligned.u32 %0;" ::"n"(RG_G));
    const int w = warp - 8, gq = lane >> 2, t = lane & 3;
    TSC(tid == 256, 5);
    GState st{lane == 0, 0u};
    {
      float d0[64], d1[64];
#pragma unroll
      for (int i = 0; i < 64; i++) asm volatile("" : "=f"(d0[i]), "=f"(d1[i]));
      auto nohook = []() {};
      const uint32_t oa = sb + SM_XR + ((lane & 7) + (lane >> 4) * 8) * 128 + (((2 * w + ((lane >> 3) & 1)) ^ (lane & 7)) << 4);
      auto sched = [&](int c) { return c <= 9 ? ds.sa + ((c * ds.sb) >> 4) : ds.sa + ((9 * ds.sb + (c - 9) * ds.sc) >> 4); };
      auto red_ptr = [&](int c2) {
        int c = c2 + g + 1; if (c >= 9) c -= 9;
        return (uint8_t*)(g_acc + (size_t)(r * 9 + c) * 8192 + w * 2048 + lane * 4);
      };
#pragma unroll 1
      for (int it = 0; it < 6; it++) {
        const bool mid = (it >= 1 && it <= 4);
        if (mid) gemm_chunk<false, true, false>(d1, d0, red_ptr(2 * it - 2), st, ds, it, true, false, 1u, 0u, sched(8 + 2 * it), nohook);
        gemm_chunk<false, false, true>(d0, d1, red_ptr(2 * it - 1), st, ds, 2 * it, mid, it == 5, (uint32_t)mid,
                                       bar + (it == 0 ? B_Y : B_OF) * 8, mid ? sched(9 + 2 * it) : 0, [&]() {
          if (it == 5) {
            wg_wait<0>();
            mbar_wait(bar + B_ACC * 8, 0);
            const float4* ap = (const float4*)red_ptr(8);
#pragma unroll
            for (int i = 0; i < 16; i++) { const float4 q = __ldcg(ap + i * 32); d1[4 * i] = q.x; d1[4 * i + 1] = q.y; d1[4 * i + 2] = q.z; d1[4 * i + 3] = q.w; }
            const float c0 = __bfloat162float(b2[g * 64 + w * 16 + gq]), c1 = __bfloat162float(b2[g * 64 + w * 16 + gq + 8]);
            mbar_wait(bar + B_XR * 8, 0);
#pragma unroll
            for (int i = 0; i < 8; i++) {
              uint32_t v[4];
              asm volatile("ldmatrix.sync.aligned.m8n8.x4.trans.shared.b16 {%0,%1,%2,%3}, [%4];" : "=r"(v[0]), "=r"(v[1]), "=r"(v[2]), "=r"(v[3]) : "r"(oa + i * 2048) : "memory");
#pragma unroll
              for (int k = 0; k < 4; k++) { d1[8 * i + 2 * k] += bf_lo(v[k]) + ((k & 1) ? c1 : c0); d1[8 * i + 2 * k + 1] += bf_hi(v[k]) + ((k & 1) ? c1 : c0); }
            }
            pin(d1);
          }
        });
        if (it == 5) break;
        gemm_drain(d0);
        if (it == 4 && st.lead) mbar_arrive(bar + (B_RESE + 8) * 8);
        TSC(tid == 256, it == 0 ? 11 : 17 + it);
        if (it == 0) {
          uint8_t* hp = g_h + (size_t)(r * 72 + g * 9) * 16384 + (2 * w) * 2048 + lane * 4;
          mbar_wait(bar + B_BIAS * 8, 0);
#pragma unroll 1
          for (int c = 1; c < 10; c++) {
            const bf16* bs = (const bf16*)(smem + SM_B1) + (c - 1) * 64 + w * 16 + gq;
            const float b0 = 0.5f * __bfloat162float(bs[0]), b1v = 0.5f * __bfloat162float(bs[8]);
#pragma unroll
            for (int i = 0; i < 64; i++) d1[i] = fmaf(d0[i], 0.5f, (i & 2) ? b1v : b0);
            pin(d1);
            if (c == 9) {
              nb_sync(NB_GEMM, 128);
              hp = smem + SM_RES + 8 * 16384 + (2 * w) * 2048 + lane * 4;
            }
            gemm_chunk<true, true, true>(d0, d1, hp, st, ds, c, true, false, (uint32_t)(c != 9), bar + B_RESF * 8, sched(c), nohook);
            hp += 16384;
            gemm_drain(d0);
            TSC(tid == 256 && (!(c & 1) || c == 9), 12 + ((c + 1) >> 1));
          }
        }
      }
      {
        gemm_drain(d0);
        TSC(tid == 256, 43);
#pragma unroll
        for (int i = 0; i < 8; i++)
          asm volatile("stmatrix.sync.aligned.m8n8.x4.trans.shared.b16 [%0], {%1,%2,%3,%4};" ::"r"(oa + i * 2048),
                       "r"(pack_bf16(d0[8 * i] + d1[8 * i], d0[8 * i + 1] + d1[8 * i + 1])), "r"(pack_bf16(d0[8 * i + 2] + d1[8 * i + 2], d0[8 * i + 3] + d1[8 * i + 3])),
                       "r"(pack_bf16(d0[8 * i + 4] + d1[8 * i + 4], d0[8 * i + 5] + d1[8 * i + 5])), "r"(pack_bf16(d0[8 * i + 6] + d1[8 * i + 6], d0[8 * i + 7] + d1[8 * i + 7])) : "memory");
        asm volatile("fence.proxy.async.shared::cta;" ::: "memory");
        nb_sync(NB_GEMM, 128);
        if (warp == 8 && elect_one()) {
          asm volatile("cp.async.bulk.tensor.2d.global.shared::cta.bulk_group [%0, {%2, %3}], [%1];" ::"l"(&tm_out), "r"(sb + SM_XR), "r"(g * 64), "r"(r * 128) : "memory");
          asm volatile("cp.async.bulk.commit_group;\ncp.async.bulk.wait_group.read 0;" ::: "memory");
        }
      }
      TSC(tid == 256, 22);
    }
  } else {
    asm volatile("setmaxnreg.inc.sync.aligned.u32 %0;" ::"n"(RG_A));
    const int gq = lane >> 2, t = lane & 3;
    const unsigned tag = *(volatile unsigned*)&g_epoch + 1u;
    uint32_t ph = 0;
    const uint32_t zr = (uint32_t)(ds.dbg >> 30), zr2 = (uint32_t)(ds.dbg >> 29), kc = 0x9F809F80u + zr;
#pragma unroll 1
    for (int j = 0; j < 4; j++) {
      const int h = g + 8 * j;
      mbar_wait_nap(bar + (B_QR + j) * 8, 0);
      TSC((tid & 127) == 0, 24 + (tid >> 7) * 8 + 2 * j);
      uint32_t q0, q1, q2, q3, q4, q5;
      float qn;
      {
        const uint8_t* qp = g_q + (size_t)(h * NRT + r) * QB + (warp * 2) * 128 + lane * 4;
        q0 = __ldcg((const uint32_t*)(qp));
        q1 = __ldcg((const uint32_t*)(qp + 128));
        q2 = __ldcg((const uint32_t*)(qp + 2048));
        q3 = __ldcg((const uint32_t*)(qp + 2048 + 128));
        q4 = (lane < 8) ? __ldcg((const uint32_t*)(qp + 4096)) : 0u;
        q5 = (lane < 8) ? __ldcg((const uint32_t*)(qp + 4096 + 128)) : 0u;
        const uint8_t* kp = g_kv + (size_t)(h * NRT + r) * KVB + (warp * 2) * 128 + lane * 4;
        const uint32_t k0 = __ldcg((const uint32_t*)(kp)), k1 = __ldcg((const uint32_t*)(kp + 128));
        const uint32_t k2 = __ldcg((const uint32_t*)(kp + 2048)), k3 = __ldcg((const uint32_t*)(kp + 2048 + 128));
        const uint32_t k4 = (lane < 8) ? __ldcg((const uint32_t*)(kp + 8192)) : 0u, k5 = (lane < 8) ? __ldcg((const uint32_t*)(kp + 8192 + 128)) : 0u;
        qn = max_sqnorm(q0, q2, q4, q1, q3, q5);
        const float kn = max_sqnorm(k0, k2, k4, k1, k3, k5);
        if (lane == 0) asm volatile("st.relaxed.gpu.global.v2.u32 [%0], {%1,%2};" ::"l"(g_kn + h * 128 + r * 8 + warp), "r"(__float_as_uint(kn) & 0x7FFFFFFFu), "r"(tag) : "memory");
        q0 = movm(q0); q1 = movm(q1); q2 = movm(q2); q3 = movm(q3); q4 = movm(q4); q5 = movm(q5);
        if (t == 2) { q4 = 0x00003F80u; q5 = 0x00003F80u; }
        if (t == 3) { q4 = 0x3F803F80u; q5 = 0x3F803F80u; }
      }
      float o[12], sa[32], sbb[32];
      uint32_t pa[16], pb[16];
#pragma unroll
      for (int i = 0; i < 12; i++) o[i] = 0.f;
      pin(o);
#define SFENCE()
#define ISSUE_S(S, off) { wgmma_rs64_t_z(S, q0, q1, q2, q3, dk0 + (off)); wgmma_rs64_t(S, q4, q5, zr, zr2, dkx + (off)); }
#define ISSUE_PV(P, off) { _Pragma("unroll") for (int k = 0; k < 4; k++) wgmma_rs24_n(o, P[4 * k], P[4 * k + 1], P[4 * k + 2], P[4 * k + 3], dv + ((off) + k * 16)); }
      {
        const uint64_t dk0 = ds.k0, dkx = ds.kx;
        mbar_wait(bar + B_KVF * 8, ph);
        wg_fence();
        ISSUE_S(sa, 0);
        wg_commit();
        wg_wait<0>();
      }
      TSC(tid == 0 && j == 0, 6);
#pragma unroll 1
      for (int s4 = 0; s4 < NRT / NKV; s4++) {
        const uint64_t z64 = (uint64_t)(uint32_t)(s4 >> 8);
        const uint64_t dk0 = ds.k0 + z64, dkx = ds.kx + z64, dv = ds.v + z64;
#pragma unroll
        for (int sl = 0; sl < NKV; sl++) {
          constexpr int SS = KVB / 16;
          const int nx = (sl + 1) % NKV;
          if (sl == NKV - 1) ph ^= 1;
          pin(sa);
          SFENCE();
          ISSUE_S(sbb, sl * SS + 64);
          wg_commit();
          uint32_t rdy = mbar_test(bar + (B_KVF + nx) * 8, ph);
          softmax_tile(sa, pa, kc);
          pin(pa);
          wg_fence();
          ISSUE_PV(pa, sl * SS);
          wg_commit();
          if (sl == NKV - 1) rdy |= (uint32_t)(s4 + 1 == NRT / NKV);
          mbar_wait_unless(rdy, bar + (B_KVF + nx) * 8, ph);
          wg_wait<1>();
          pin(sbb);
          if (sl > 0 || s4 > 0) nb_arrive(NB_KVE + (sl + NKV - 1) % NKV, 288);
          SFENCE();
          ISSUE_S(sa, nx * SS);
          wg_commit();
          softmax_tile(sbb, pb, kc);
          pin(pb);
          wg_fence();
          ISSUE_PV(pb, sl * SS + 64);
          wg_commit();
          wg_wait<1>();
        }
      }
      wg_wait<0>();
      pin(o);
      nb_arrive(NB_KVE + NKV - 1, 288);
      float i0, i1;
      {
        const float kmx = *(const volatile float*)(smem + SM_TMP + j * 4);
        i0 = __frcp_rn(__shfl_sync(~0u, o[9], (lane & ~3) + 2)); i1 = __frcp_rn(__shfl_sync(~0u, o[11], (lane & ~3) + 2));
        float a0 = fmaxf(fmaxf(fabsf(o[0]), fabsf(o[1])), fmaxf(fabsf(o[4]), fabsf(o[5]))), a1 = fmaxf(fmaxf(fabsf(o[2]), fabsf(o[3])), fmaxf(fabsf(o[6]), fabsf(o[7])));
        float sum = (o[0] + o[1] + o[4] + o[5]) + (o[2] + o[3] + o[6] + o[7]);
        if (t == 1) sum += (o[8] + o[9]) + (o[10] + o[11]);
        const bool ok = (qn * kmx <= 3300.f) && (a0 * i0 >= 1e-12f) && (a1 * i1 >= 1e-12f) && (fabsf(sum) <= 3e38f) && !(ds.dbg & 1);
        if (!__all_sync(~0u, ok)) {
          attn_safe(o, g_kv + (size_t)h * NRT * KVB + lane * 4, q0, q1, q2, q3, t == 0 ? q4 : 0u, t == 0 ? q5 : 0u);
          i0 = __frcp_rn(__shfl_sync(~0u, o[9], (lane & ~3) + 2)); i1 = __frcp_rn(__shfl_sync(~0u, o[11], (lane & ~3) + 2));
        }
      }
      {
        uint8_t* ob = g_o + (size_t)r * 147456 + (warp * 2) * 128 + t * 4;
#pragma unroll
        for (int n = 0; n < 3; n++) {
          const uint32_t v0 = movm(pack_bf16(o[4 * n] * i0, o[4 * n + 1] * i0)), v1 = movm(pack_bf16(o[4 * n + 2] * i1, o[4 * n + 3] * i1));
          const int col = h * 18 + (n < 2 ? n * 8 + gq : 14 + gq);
          if (n < 2 || (gq >> 1) == 1) {
            stg32(ob + (col >> 3) * 2048 + (col & 7) * 16, v0);
            stg32(ob + (col >> 3) * 2048 + (col & 7) * 16 + 128, v1);
          }
        }
      }
      __syncwarp();
      if (lane == 0 && j < 3) mbar_arrive(bar + (B_O + j) * 8);
      TSC((tid & 127) == 0, 24 + (tid >> 7) * 8 + 2 * j + 1);
    }
    if (warp >= 4) {
      const uint4* src = (const uint4*)(g_o + (size_t)r * 147456 + 54 * 2048) + (tid - 128);
      uint4 v[18];
#pragma unroll
      for (int i = 0; i < 18; i++) v[i].x = ~0u;
      int it = 0;
      bool ok;
      do {
        ok = true;
#pragma unroll
        for (int i = 0; i < 18; i++)
          if (v[i].x == ~0u || v[i].y == ~0u || v[i].z == ~0u || v[i].w == ~0u)
            asm volatile("ld.relaxed.gpu.global.v4.u32 {%0,%1,%2,%3}, [%4];" : "=r"(v[i].x), "=r"(v[i].y), "=r"(v[i].z), "=r"(v[i].w) : "l"(src + i * 128) : "memory");
#pragma unroll
        for (int i = 0; i < 18; i++) ok = ok && v[i].x != ~0u && v[i].y != ~0u && v[i].z != ~0u && v[i].w != ~0u;
        ok = __all_sync(~0u, ok);
        if (!ok) __nanosleep(100);
      } while (!ok && ++it < 4000000);
      TSC(tid == 128, 42);
      mbar_wait_nap(bar + (B_RESE + 8) * 8, 0);
#pragma unroll
      for (int i = 0; i < 18; i++) *(uint4*)(smem + SM_RES + 54 * 2048 + (i * 128 + tid - 128) * 16) = v[i];
      asm volatile("fence.proxy.async.shared::cta;" ::: "memory");
      __syncwarp();
      if (lane == 0) { mbar_arrive(bar + (B_OF + 6) * 8); mbar_arrive(bar + (B_OF + 7) * 8); mbar_arrive(bar + (B_OF + 8) * 8); }
    } else {
      float d2[8];
      const size_t eo = (size_t)(r * 128 + g * 16 + gq) * D_ + 512 + warp * 16 + t * 2;
#pragma unroll
      for (int i = 0; i < 4; i++) {
        const uint32_t v = movm(__ldg((const uint32_t*)(x + eo + (i >> 1) * (8 * D_) + (i & 1) * 8)));
        const float c = __bfloat162float(b2[512 + warp * 16 + gq + (i & 1) * 8]);
        d2[2 * i] = bf_lo(v) + c; d2[2 * i + 1] = bf_hi(v) + c;
      }
      pin(d2);
      float4 av[2];
#pragma unroll 1
      for (int j4 = 0; j4 < 3; j4++) {
        const uint64_t da = ds.w + (uint64_t)(SM_KV / 16), db = ds.h + (uint64_t)(uint32_t)(j4 * 3072 + g * 16);
        if (j4 == 2) {
          mbar_wait_nap(bar + B_ACC * 8, 0);
          const float4* ap2 = (const float4*)(g_acc + (size_t)(r * 9 + 8) * 8192 + warp * 2048 + (2 * g) * 128 + lane * 4);
          av[0] = __ldcg(ap2); av[1] = __ldcg(ap2 + 32);
        }
#pragma unroll
        for (int s = 0; s < 4; s++) {
          if (s < 3) mbar_wait_nap(bar + (B_OF + j4 * 3 + s) * 8, 0);
          mbar_wait(bar + (B_KVF + s) * 8, ph);
          wg_fence();
#pragma unroll
          for (int u = 0; u < 3; u++) wgmma_ss16_tt(d2, da + (s * (WST / 16) + u * 128), db + (3 * s + u) * 256, 1);
          wg_commit();
          wg_wait<0>();
          if (j4 < 2) nb_arrive(NB_KVE + s, 160);
        }
        ph ^= 1;
      }
      pin(d2);
      uint8_t* op2 = (uint8_t*)(out + eo);
#pragma unroll
      for (int i = 0; i < 2; i++) {
        stg32(op2 + i * (8 * D_ * 2), movm(pack_bf16(d2[4 * i] + av[i].x, d2[4 * i + 1] + av[i].y)));
        stg32(op2 + i * (8 * D_ * 2) + 16, movm(pack_bf16(d2[4 * i + 2] + av[i].z, d2[4 * i + 3] + av[i].w)));
      }
      TSC(tid == 0, 40);
    }
  }
}

typedef CUresult (*enc_fn)(CUtensorMap*, CUtensorMapDataType, cuuint32_t, void*, const cuuint64_t*, const cuuint64_t*,
                           const cuuint32_t*, const cuuint32_t*, CUtensorMapInterleave, CUtensorMapSwizzle,
                           CUtensorMapL2promotion, CUtensorMapFloatOOBfill);
static void make_map(enc_fn enc, CUtensorMap* tm, const void* p, int cols, int rows, int bc, int br) {
  cuuint64_t gd[2] = {(cuuint64_t)cols, (cuuint64_t)rows};
  cuuint64_t gs[1] = {(cuuint64_t)cols * 2};
  cuuint32_t bx[2] = {(cuuint32_t)bc, (cuuint32_t)br};
  cuuint32_t es[2] = {1, 1};
  enc(tm, CU_TENSOR_MAP_DATA_TYPE_BFLOAT16, 2, (void*)p, gd, gs, bx, es, CU_TENSOR_MAP_INTERLEAVE_NONE,
      CU_TENSOR_MAP_SWIZZLE_128B, CU_TENSOR_MAP_L2_PROMOTION_L2_256B, CU_TENSOR_MAP_FLOAT_OOB_FILL_NONE);
}

extern "C" void kernel_launch(void* const* d_in, const int* in_sizes, int n_in, void* d_out, int out_size) {
  const bf16* x = (const bf16*)d_in[0];
  const bf16* wqkv = (const bf16*)d_in[1];
  const bf16* wo = (const bf16*)d_in[2];
  const bf16* w1 = (const bf16*)d_in[4];
  const bf16* b1 = (const bf16*)d_in[5];
  const bf16* w2 = (const bf16*)d_in[6];
  const bf16* b2 = (const bf16*)d_in[7];
  static enc_fn enc = nullptr;
  if (!enc) {
    void* fn = nullptr;
    cudaDriverEntryPointQueryResult qr;
    cudaGetDriverEntryPoint("cuTensorMapEncodeTiled", &fn, cudaEnableDefault, &qr);
    enc = (enc_fn)fn;
    cudaFuncSetAttribute(main_kernel, cudaFuncAttributeMaxDynamicSharedMemorySize, SM_TOTAL);
  }
  CUtensorMap tm_x, tm_wqkv, tm_w1, tm_w2, tm_wo, tm_out;
  make_map(enc, &tm_out, d_out, D_, S_, 64, 128);
  make_map(enc, &tm_x, x, D_, S_, 64, 128);
  make_map(enc, &tm_wqkv, wqkv, 3 * D_, D_, 64, 96);
  make_map(enc, &tm_w1, w1, F_, D_, 64, 48);
  make_map(enc, &tm_w2, w2, D_, F_, 64, 48);
  make_map(enc, &tm_wo, wo, D_, D_, 64, 48);
  auto mk = [](uint32_t addr, uint32_t lbo, uint32_t sbo, uint32_t swz) {
    return ((uint64_t)desc_hi(sbo, swz) << 32) | (uint64_t)((addr >> 4) | desc_lbo(lbo));
  };
  Descs ds;
  ds.w = mk(SB0, 0, 1024, 1);
  ds.x = mk(SB0 + SM_RES, 0, 1024, 1);
  ds.h = mk(SB0 + SM_RES, 2048, 128, 0);
  ds.k0 = mk(SB0 + SM_KV, 2048, 128, 0);
  ds.kx = mk(SB0 + SM_KV + 8192, 0, 128, 0);
  ds.v = mk(SB0 + SM_KV + 4096, 128, 2048, 0);
  ds.dbg = 0; ds.sa = 0; ds.sb = 64; ds.sc = 52;
  main_kernel<<<NRT * NG + 4, 512, SM_TOTAL>>>(tm_x, tm_wqkv, tm_w1, tm_w2, tm_wo, tm_out, ds, x, b1, b2, (bf16*)d_out,
                                          (const uint8_t*)wqkv, (const uint8_t*)w1, (const uint8_t*)w2, (const uint8_t*)wo);
}
```

```cpp
#include <cuda_runtime.h>
#include <cuda_bf16.h>
#include <cuda.h>
#include <stdint.h>

typedef __nv_bfloat16 bf16;

constexpr int S_ = 2048, D_ = 576, F_ = 4608, H_ = 32, DH_ = 18;
constexpr int NRT = 16;
constexpr int NG = 8;

constexpr int KVB = 10240;
constexpr int QB = 4096;
__device__ __align__(1024) uint8_t g_y[NRT * 147456];
__device__ __align__(1024) uint8_t g_o[NRT * 147456];
__device__ __align__(1024) float2 g_st[S_];
__device__ __align__(1024) uint8_t g_q[H_ * NRT * QB];
__device__ __align__(1024) uint8_t g_kv[H_ * NRT * KVB];
__device__ __align__(1024) uint8_t g_h[NRT * 72 * 16384];
__device__ __align__(1024) float g_acc[NRT * 9 * 8192];
struct __align__(128) Flag { unsigned v; unsigned pad[31]; };
struct Flags {
  Flag ln[NRT];
  Flag red[NRT];
  Flag ocnt[NRT * 4];
  Flag qkv[32];
  Flag done;
};
__device__ Flags g_flags;
__device__ unsigned g_epoch;
__device__ __align__(1024) uint2 g_kn[H_ * 32];
#define TSC(cond, idx) do {} while (0)
#define TSG(cond, idx) do {} while (0)

__device__ __forceinline__ uint32_t smem_u32(const void* p) { return (uint32_t)__cvta_generic_to_shared(p); }
__device__ __forceinline__ void wg_fence() { asm volatile("wgmma.fence.sync.aligned;" ::: "memory"); }
__device__ __forceinline__ void wg_commit() { asm volatile("wgmma.commit_group.sync.aligned;" ::: "memory"); }
template <int N> __device__ __forceinline__ void wg_wait() { asm volatile("wgmma.wait_group.sync.aligned %0;" ::"n"(N) : "memory"); }
template <int N> __device__ __forceinline__ void pin(float (&d)[N]) {
#pragma unroll
  for (int i = 0; i < N; i++) asm volatile("" : "+f"(d[i])::"memory");
}
template <int N> __device__ __forceinline__ void pin(uint32_t (&d)[N]) {
#pragma unroll
  for (int i = 0; i < N; i++) asm volatile("" : "+r"(d[i])::"memory");
}
__device__ __forceinline__ uint64_t mkdesc(uint32_t lo, uint32_t hi) { return ((uint64_t)hi << 32) | lo; }
__host__ __device__ constexpr uint32_t desc_lbo(uint32_t lbo) { return (lbo >> 4) << 16; }
__host__ __device__ constexpr uint32_t desc_hi(uint32_t sbo, uint32_t swz) { return (sbo >> 4) | (swz << 30); }

__device__ __forceinline__ void mbar_init(uint32_t bar, int cnt) { asm volatile("mbarrier.init.shared::cta.b64 [%0], %1;" ::"r"(bar), "r"(cnt)); }
__device__ __forceinline__ void mbar_expect(uint32_t bar, uint32_t bytes) {
  asm volatile("mbarrier.arrive.expect_tx.shared::cta.b64 _, [%0], %1;" ::"r"(bar), "r"(bytes) : "memory");
}
__device__ __forceinline__ void mbar_arrive(uint32_t bar) { asm volatile("mbarrier.arrive.shared::cta.b64 _, [%0];" ::"r"(bar) : "memory"); }
__device__ __forceinline__ uint32_t mbar_test(uint32_t bar, uint32_t ph) {
  uint32_t ok;
  asm volatile("{\n.reg .pred p;\nmbarrier.test_wait.parity.shared::cta.b64 p, [%1], %2;\nselp.u32 %0,1,0,p;\n}" : "=r"(ok) : "r"(bar), "r"(ph) : "memory");
  return ok;
}
__device__ __forceinline__ void mbar_wait(uint32_t bar, uint32_t ph) {
  asm volatile("{\n.reg .pred p;\nMW_LOOP:\nmbarrier.try_wait.parity.shared::cta.b64 p, [%0], %1;\n@!p bra MW_LOOP;\n}" ::"r"(bar), "r"(ph) : "memory");
}
__device__ __forceinline__ void mbar_wait_nap(uint32_t bar, uint32_t ph) {
  asm volatile("{\n.reg .pred p;\nMN_LOOP:\nmbarrier.try_wait.parity.shared::cta.b64 p, [%0], %1;\n@p bra MN_DONE;\nnanosleep.u32 100;\nbra MN_LOOP;\nMN_DONE:\n}" ::"r"(bar), "r"(ph) : "memory");
}
__device__ __forceinline__ void mbar_wait_unless(uint32_t ok, uint32_t bar, uint32_t ph) {
  asm volatile(
      "{\n.reg .pred p;\n"
      "setp.ne.u32 p, %2, 0;\n"
      "@p bra MW_DONE;\n"
      "MW_LOOP:\nmbarrier.try_wait.parity.shared::cta.b64 p, [%0], %1;\n@!p bra MW_LOOP;\n"
      "MW_DONE:\n}" ::"r"(bar), "r"(ph), "r"(ok) : "memory");
}
__device__ __forceinline__ void mbar_wait_slow(uint32_t bar, uint32_t ph) {
  asm volatile(
      "{\n.reg .pred p;\n.reg .u32 c;\n"
      "mov.u32 c, 0;\n"
      "MS_LOOP:\n"
      "mbarrier.try_wait.parity.shared::cta.b64 p, [%0], %1;\n"
      "@p bra MS_DONE;\n"
      "nanosleep.u32 64;\n"
      "add.u32 c, c, 1;\n"
      "setp.lt.u32 p, c, 1000000;\n"
      "@p bra MS_LOOP;\n"
      "trap;\n"
      "MS_DONE:\n}" ::"r"(bar), "r"(ph) : "memory");
}
__device__ __forceinline__ void mbar_wait_sleep(uint32_t bar, uint32_t ph) {
  asm volatile(
      "{\n.reg .pred p;\n.reg .u32 c;\n"
      "mov.u32 c, 0;\n"
      "MS_LOOP:\n"
      "mbarrier.try_wait.parity.shared::cta.b64 p, [%0], %1;\n"
      "@p bra MS_DONE;\n"
      "nanosleep.u32 250;\n"
      "add.u32 c, c, 1;\n"
      "setp.lt.u32 p, c, 1000000;\n"
      "@p bra MS_LOOP;\n"
      "trap;\n"
      "MS_DONE:\n}" ::"r"(bar), "r"(ph) : "memory");
}
__device__ __forceinline__ void nb_sync(int id, int n) { asm volatile("bar.sync %0, %1;" ::"r"(id), "r"(n) : "memory"); }
__device__ __forceinline__ void nb_arrive(int id, int n) { asm volatile("bar.arrive %0, %1;" ::"r"(id), "r"(n) : "memory"); }
__device__ __forceinline__ void st32(void* p, uint32_t v) { asm volatile("st.b32 [%0], %1;" ::"l"(p), "r"(v) : "memory"); }
__device__ __forceinline__ void stg32(void* p, uint32_t v) { asm volatile("st.global.b32 [%0], %1;" ::"l"(p), "r"(v) : "memory"); }
__device__ __forceinline__ void sts32(uint32_t a, uint32_t v) { asm volatile("st.shared.b32 [%0], %1;" ::"r"(a), "r"(v) : "memory"); }
__device__ __forceinline__ bool elect_one() {
  uint32_t p;
  asm volatile("{\n.reg .pred q;\nelect.sync _|q, 0xffffffff;\nselp.u32 %0, 1, 0, q;\n}" : "=r"(p));
  return p != 0;
}
__device__ __forceinline__ void tma2d(uint32_t dst, const CUtensorMap* tm, int c0, int c1, uint32_t bar) {
  asm volatile("cp.async.bulk.tensor.2d.shared::cluster.global.mbarrier::complete_tx::bytes [%0], [%1, {%3, %4}], [%2];" ::"r"(dst), "l"(tm), "r"(bar), "r"(c0), "r"(c1) : "memory");
}
__device__ __forceinline__ uint64_t policy_evict_first() {
  uint64_t p;
  asm volatile("createpolicy.fractional.L2::evict_first.b64 %0, 1.0;" : "=l"(p));
  return p;
}
__device__ __forceinline__ void tma2d_h(uint32_t dst, const CUtensorMap* tm, int c0, int c1, uint32_t bar, uint64_t pol) {
  asm volatile("cp.async.bulk.tensor.2d.shared::cluster.global.mbarrier::complete_tx::bytes.L2::cache_hint [%0], [%1, {%3, %4}], [%2], %5;" ::"r"(dst), "l"(tm), "r"(bar), "r"(c0), "r"(c1), "l"(pol) : "memory");
}
__device__ __forceinline__ void bulk_ld_h(uint32_t dst, const void* src, uint32_t bytes, uint32_t bar, uint64_t pol) {
  asm volatile("cp.async.bulk.shared::cluster.global.mbarrier::complete_tx::bytes.L2::cache_hint [%0], [%1], %2, [%3], %4;" ::"r"(dst), "l"(src), "r"(bytes), "r"(bar), "l"(pol) : "memory");
}
__device__ __forceinline__ void bulk_ld(uint32_t dst, const void* src, uint32_t bytes, uint32_t bar) {
  asm volatile("cp.async.bulk.shared::cluster.global.mbarrier::complete_tx::bytes [%0], [%1], %2, [%3];" ::"r"(dst), "l"(src), "r"(bytes), "r"(bar) : "memory");
}
__device__ __forceinline__ void l2_prefetch(const void* p, uint32_t bytes) {
  asm volatile("cp.async.bulk.prefetch.L2.global [%0], %1;" ::"l"(p), "r"(bytes) : "memory");
}
__device__ __forceinline__ void flag_wait(const Flag* p, unsigned target) {
  asm volatile(
      "{\n.reg .pred p;\n.reg .u32 c, v;\n"
      "mov.u32 c, 0;\n"
      "FW_LOOP:\n"
      "ld.acquire.gpu.global.u32 v, [%0];\n"
      "setp.ge.u32 p, v, %1;\n"
      "@p bra FW_DONE;\n"
      "nanosleep.u32 100;\n"
      "add.u32 c, c, 1;\n"
      "setp.lt.u32 p, c, 4000000;\n"
      "@p bra FW_LOOP;\n"
      "trap;\n"
      "FW_DONE:\n}" ::"l"(p), "r"(target) : "memory");
}
__device__ __forceinline__ void flag_wait_sleep(const Flag* p, unsigned target) {
  asm volatile(
      "{\n.reg .pred p;\n.reg .u32 c, v;\n"
      "mov.u32 c, 0;\n"
      "FW_LOOP:\n"
      "ld.acquire.gpu.global.u32 v, [%0];\n"
      "setp.ge.u32 p, v, %1;\n"
      "@p bra FW_DONE;\n"
      "nanosleep.u32 500;\n"
      "add.u32 c, c, 1;\n"
      "setp.lt.u32 p, c, 1000000;\n"
      "@p bra FW_LOOP;\n"
      "trap;\n"
      "FW_DONE:\n}" ::"l"(p), "r"(target) : "memory");
}
__device__ __forceinline__ void flag_add(Flag* p) {
  asm volatile("fence.acq_rel.gpu;\nred.relaxed.gpu.global.add.u32 [%0], 1;" ::"l"(p) : "memory");
}
__device__ __forceinline__ void fence_async_all() { asm volatile("fence.proxy.async;" ::: "memory"); }
__device__ __forceinline__ uint32_t pack_bf16(float lo, float hi) {
  uint32_t r;
  asm("cvt.rn.bf16x2.f32 %0, %1, %2;" : "=r"(r) : "f"(hi), "f"(lo));
  return r;
}
__device__ __forceinline__ float ex2f(float x) { float y; asm("ex2.approx.ftz.f32 %0, %1;" : "=f"(y) : "f"(x)); return y; }
__device__ __forceinline__ float rcp_fast(float x) { float y; asm("rcp.approx.ftz.f32 %0, %1;" : "=f"(y) : "f"(x)); return y; }
__device__ __forceinline__ float tanh_fast(float x) { float y; asm("tanh.approx.f32 %0, %1;" : "=f"(y) : "f"(x)); return y; }
__device__ __forceinline__ float bf_lo(uint32_t v) { return __uint_as_float(v << 16); }
__device__ __forceinline__ float bf_hi(uint32_t v) { return __uint_as_float(v & 0xFFFF0000u); }
__device__ __forceinline__ uint32_t movm(uint32_t a) {
  uint32_t d;
  asm volatile("movmatrix.sync.aligned.m8n8.trans.b16 %0, %1;" : "=r"(d) : "r"(a));
  return d;
}

__device__ __forceinline__ void wgmma_ss136_tn(float (&d)[68], uint64_t da, uint64_t db, int sd) {
  asm volatile("{\n.reg .pred p;\nsetp.ne.b32 p, %70, 0;\n"
    "wgmma.mma_async.sync.aligned.m64n136k16.f32.bf16.bf16 {%0, %1, %2, %3, %4, %5, %6, %7, %8, %9, %10, %11, %12, %13, %14, %15, %16, %17, %18, %19, %20, %21, %22, %23, %24, %25, %26, %27, %28, %29, %30, %31, %32, %33, %34, %35, %36, %37, %38, %39, %40, %41, %42, %43, %44, %45, %46, %47, %48, %49, %50, %51, %52, %53, %54, %55, %56, %57, %58, %59, %60, %61, %62, %63, %64, %65, %66, %67}, %68, %69, p, 1, 1, 1, 0;\n}\n"
    : "+f"(d[0]), "+f"(d[1]), "+f"(d[2]), "+f"(d[3]), "+f"(d[4]), "+f"(d[5]), "+f"(d[6]), "+f"(d[7]), "+f"(d[8]), "+f"(d[9]), "+f"(d[10]), "+f"(d[11]), "+f"(d[12]), "+f"(d[13]), "+f"(d[14]), "+f"(d[15]), "+f"(d[16]), "+f"(d[17]), "+f"(d[18]), "+f"(d[19]), "+f"(d[20]), "+f"(d[21]), "+f"(d[22]), "+f"(d[23]), "+f"(d[24]), "+f"(d[25]), "+f"(d[26]), "+f"(d[27]), "+f"(d[28]), "+f"(d[29]), "+f"(d[30]), "+f"(d[31]), "+f"(d[32]), "+f"(d[33]), "+f"(d[34]), "+f"(d[35]), "+f"(d[36]), "+f"(d[37]), "+f"(d[38]), "+f"(d[39]), "+f"(d[40]), "+f"(d[41]), "+f"(d[42]), "+f"(d[43]), "+f"(d[44]), "+f"(d[45]), "+f"(d[46]), "+f"(d[47]), "+f"(d[48]), "+f"(d[49]), "+f"(d[50]), "+f"(d[51]), "+f"(d[52]), "+f"(d[53]), "+f"(d[54]), "+f"(d[55]), "+f"(d[56]), "+f"(d[57]), "+f"(d[58]), "+f"(d[59]), "+f"(d[60]), "+f"(d[61]), "+f"(d[62]), "+f"(d[63]), "+f"(d[64]), "+f"(d[65]), "+f"(d[66]), "+f"(d[67])
    : "l"(da), "l"(db), "r"(sd));
}
__device__ __forceinline__ void wgmma_ss128_tt(float (&d)[64], uint64_t da, uint64_t db, int sd) {
  asm volatile("{\n.reg .pred p;\nsetp.ne.b32 p, %66, 0;\n"
    "wgmma.mma_async.sync.aligned.m64n128k16.f32.bf16.bf16 {%0, %1, %2, %3, %4, %5, %6, %7, %8, %9, %10, %11, %12, %13, %14, %15, %16, %17, %18, %19, %20, %21, %22, %23, %24, %25, %26, %27, %28, %29, %30, %31, %32, %33, %34, %35, %36, %37, %38, %39, %40, %41, %42, %43, %44, %45, %46, %47, %48, %49, %50, %51, %52, %53, %54, %55, %56, %57, %58, %59, %60, %61, %62, %63}, %64, %65, p, 1, 1, 1, 1;\n}\n"
    : "+f"(d[0]), "+f"(d[1]), "+f"(d[2]), "+f"(d[3]), "+f"(d[4]), "+f"(d[5]), "+f"(d[6]), "+f"(d[7]), "+f"(d[8]), "+f"(d[9]), "+f"(d[10]), "+f"(d[11]), "+f"(d[12]), "+f"(d[13]), "+f"(d[14]), "+f"(d[15]), "+f"(d[16]), "+f"(d[17]), "+f"(d[18]), "+f"(d[19]), "+f"(d[20]), "+f"(d[21]), "+f"(d[22]), "+f"(d[23]), "+f"(d[24]), "+f"(d[25]), "+f"(d[26]), "+f"(d[27]), "+f"(d[28]), "+f"(d[29]), "+f"(d[30]), "+f"(d[31]), "+f"(d[32]), "+f"(d[33]), "+f"(d[34]), "+f"(d[35]), "+f"(d[36]), "+f"(d[37]), "+f"(d[38]), "+f"(d[39]), "+f"(d[40]), "+f"(d[41]), "+f"(d[42]), "+f"(d[43]), "+f"(d[44]), "+f"(d[45]), "+f"(d[46]), "+f"(d[47]), "+f"(d[48]), "+f"(d[49]), "+f"(d[50]), "+f"(d[51]), "+f"(d[52]), "+f"(d[53]), "+f"(d[54]), "+f"(d[55]), "+f"(d[56]), "+f"(d[57]), "+f"(d[58]), "+f"(d[59]), "+f"(d[60]), "+f"(d[61]), "+f"(d[62]), "+f"(d[63])
    : "l"(da), "l"(db), "r"(sd));
}
__device__ __forceinline__ void wgmma_ss16_tt(float (&d)[8], uint64_t da, uint64_t db, int sd) {
  asm volatile("{\n.reg .pred p;\nsetp.ne.b32 p, %10, 0;\n"
    "wgmma.mma_async.sync.aligned.m64n16k16.f32.bf16.bf16 {%0, %1, %2, %3, %4, %5, %6, %7}, %8, %9, p, 1, 1, 1, 1;\n}\n"
    : "+f"(d[0]), "+f"(d[1]), "+f"(d[2]), "+f"(d[3]), "+f"(d[4]), "+f"(d[5]), "+f"(d[6]), "+f"(d[7])
    : "l"(da), "l"(db), "r"(sd));
}
__device__ __forceinline__ void wgmma_rs64_t_z(float (&d)[32], uint32_t a0, uint32_t a1, uint32_t a2, uint32_t a3, uint64_t db) {
  asm volatile("{\n.reg .pred p;\nsetp.ne.b32 p, 0, 0;\n"
    "wgmma.mma_async.sync.aligned.m64n64k16.f32.bf16.bf16 {%0, %1, %2, %3, %4, %5, %6, %7, %8, %9, %10, %11, %12, %13, %14, %15, %16, %17, %18, %19, %20, %21, %22, %23, %24, %25, %26, %27, %28, %29, %30, %31}, {%32, %33, %34, %35}, %36, p, 1, 1, 1;\n}\n"
    : "=f"(d[0]), "=f"(d[1]), "=f"(d[2]), "=f"(d[3]), "=f"(d[4]), "=f"(d[5]), "=f"(d[6]), "=f"(d[7]), "=f"(d[8]), "=f"(d[9]), "=f"(d[10]), "=f"(d[11]), "=f"(d[12]), "=f"(d[13]), "=f"(d[14]), "=f"(d[15]), "=f"(d[16]), "=f"(d[17]), "=f"(d[18]), "=f"(d[19]), "=f"(d[20]), "=f"(d[21]), "=f"(d[22]), "=f"(d[23]), "=f"(d[24]), "=f"(d[25]), "=f"(d[26]), "=f"(d[27]), "=f"(d[28]), "=f"(d[29]), "=f"(d[30]), "=f"(d[31])
    : "r"(a0), "r"(a1), "r"(a2), "r"(a3), "l"(db));
}
__device__ __forceinline__ void wgmma_rs64_t(float (&d)[32], uint32_t a0, uint32_t a1, uint32_t a2, uint32_t a3, uint64_t db) {
  asm volatile("{\n.reg .pred p;\nsetp.ne.b32 p, 1, 0;\n"
    "wgmma.mma_async.sync.aligned.m64n64k16.f32.bf16.bf16 {%0, %1, %2, %3, %4, %5, %6, %7, %8, %9, %10, %11, %12, %13, %14, %15, %16, %17, %18, %19, %20, %21, %22, %23, %24, %25, %26, %27, %28, %29, %30, %31}, {%32, %33, %34, %35}, %36, p, 1, 1, 1;\n}\n"
    : "+f"(d[0]), "+f"(d[1]), "+f"(d[2]), "+f"(d[3]), "+f"(d[4]), "+f"(d[5]), "+f"(d[6]), "+f"(d[7]), "+f"(d[8]), "+f"(d[9]), "+f"(d[10]), "+f"(d[11]), "+f"(d[12]), "+f"(d[13]), "+f"(d[14]), "+f"(d[15]), "+f"(d[16]), "+f"(d[17]), "+f"(d[18]), "+f"(d[19]), "+f"(d[20]), "+f"(d[21]), "+f"(d[22]), "+f"(d[23]), "+f"(d[24]), "+f"(d[25]), "+f"(d[26]), "+f"(d[27]), "+f"(d[28]), "+f"(d[29]), "+f"(d[30]), "+f"(d[31])
    : "r"(a0), "r"(a1), "r"(a2), "r"(a3), "l"(db));
}
__device__ __forceinline__ void wgmma_rs24_n(float (&d)[12], uint32_t a0, uint32_t a1, uint32_t a2, uint32_t a3, uint64_t db) {
  asm volatile("{\n.reg .pred p;\nsetp.ne.b32 p, 1, 0;\n"
    "wgmma.mma_async.sync.aligned.m64n24k16.f32.bf16.bf16 {%0, %1, %2, %3, %4, %5, %6, %7, %8, %9, %10, %11}, {%12, %13, %14, %15}, %16, p, 1, 1, 0;\n}\n"
    : "+f"(d[0]), "+f"(d[1]), "+f"(d[2]), "+f"(d[3]), "+f"(d[4]), "+f"(d[5]), "+f"(d[6]), "+f"(d[7]), "+f"(d[8]), "+f"(d[9]), "+f"(d[10]), "+f"(d[11])
    : "r"(a0), "r"(a1), "r"(a2), "r"(a3), "l"(db));
}

constexpr uint32_t SB0 = 0x400;
constexpr int NW = 6, WST = 6144, NKV = 4;
constexpr int BST = 12288;
constexpr int SM_RES = 0;
constexpr int SM_KV = 147456;
constexpr int SM_W = SM_KV + NKV * KVB;
constexpr int SM_XR = SM_KV + 4 * WST;
constexpr int SM_Q = SM_W + NW * WST;
constexpr int SM_B1 = SM_Q + QB;
constexpr int XP = 17408, SM_BIG = 9 * XP;
constexpr int SM_S2 = SM_BIG + 6 * BST;
constexpr int SM_TMP = SM_S2 + 1024;
constexpr int SM_BAR = SM_TMP + 192;
constexpr int SM_TOTAL = SM_BAR + 768;
static_assert(SM_B1 + 1152 <= SM_TMP, "smem");
enum { B_RESE = 0, B_RAW = 9, B_H7 = 18, B_RED,   B_O, B_LN = B_O + 3,   B_RESF, B_WF = B_RESF + 9, B_KVF = B_WF + NW,
       B_ACC = B_KVF + NKV, B_Y, B_OF = B_Y + 9, B_STAT = B_OF + 9, B_XR, B_BIAS, B_TAB, B_QR, B_BIG = B_QR + 4, B_X, B_BF = B_X + 9, B_COUNT = B_BF + 6 };
constexpr int B_H8 = B_RESF + 8;
enum { NB_H6 = 0, NB_WE = 1, NB_KVE = NB_WE + NW, NB_GEMM = NB_KVE + NKV, NB_EPI };
static_assert(NB_EPI + 2 <= 15, "named barriers");
static_assert(B_COUNT * 8 <= 768, "barriers");
static_assert(SM_TOTAL <= 232448, "smem");
struct Descs { uint64_t w, x, h, k0, kx, v; int dbg, sa, sb, sc; };

#define XMASK 0x55
constexpr uint32_t POLY_MASK = XMASK;
#define RG_A 152
#define RG_G 168
#define RG_P 40
static_assert(2 * RG_A + RG_G + RG_P <= 512, "registers");
#define NAP 150
#define XZR 0
constexpr int ZROUND = XZR;
#define PFD 2
#define XTHR 0
constexpr uint32_t MAGIC_P = 0x43DF, MAGIC_M = 0x3F15;

__device__ __forceinline__ int qkv_chunk(int p) { return (p % 3) * 9 + p / 3; }

__device__ __forceinline__ float gelu_half(float w) {
  float p = fmaf(w * w, 8.0f * 0.044715f * 0.7978845608028654f, 2.0f * 0.7978845608028654f);
  float t = tanh_fast(w * p);
  return fmaf(w, t, w);
}

struct GState { bool lead; uint32_t ready; };

template <bool GELU, bool DRAINED, bool RES, class F>
__device__ __forceinline__ void gemm_chunk(float (&cur)[64], float (&prev)[64], uint8_t* gp, GState& st, const Descs& ds,
                                           int sig, bool do_epi, bool accum, uint32_t nores, uint32_t resbar, int target, F&& hook) {
  constexpr uint32_t bar = SB0 + SM_BAR;
  int prog;
  const uint64_t z = (uint64_t)(uint32_t)(sig >> 8);
  const uint64_t da = ds.w + z, da2 = ds.w + (uint64_t)(uint32_t)(sig >> 9), db = ds.h + z;
#pragma unroll
  for (int j = 0; j < 12; j++) {
    if (j == 9) hook();
    if (RES) {
      const int b0 = (j == 0) ? 0 : (3 * j - 1) / 4 + 1, b1 = (3 * j + 2) / 4;
#pragma unroll
      for (int b = b0; b <= b1; b++) mbar_wait_unless(nores, resbar + b * 8, 0);
    }
    mbar_wait_unless(st.ready, bar + (B_WF + j % NW) * 8, (j / NW) & 1);
    if (j % 4 == 0) asm volatile("ld.volatile.shared.s32 %0, [%1];" : "=r"(prog) : "r"(SB0 + SM_TMP + 32));
    wg_fence();
#pragma unroll
    for (int u = 0; u < 3; u++) {
      const int ks = 3 * j + u;
      wgmma_ss128_tt(cur, (j < NW ? da : da2) + ((SM_W + (NW - 1 - j % NW) * WST) / 16 + u * 128), db + ks * 256, ks != 0 || accum);
    }
    wg_commit();
    st.ready = mbar_test(bar + (B_WF + (j + 1) % NW) * 8, ((j + 1) / NW) & 1);
    const int e = DRAINED ? j : j - 1;
    if (GELU) {
      if (e < 10) {
#pragma unroll
        for (int i = (32 * e) / 10; i < (32 * (e + 1)) / 10; i++)
          st32(gp + (i >> 1) * 128 + (i & 1) * 2048, pack_bf16(gelu_half(prev[2 * i]), gelu_half(prev[2 * i + 1])));
      }
    } else if (e >= 0 && e < 8) {
      auto red = [&](int i, uint32_t on) {
        asm volatile("{\n.reg .pred p;\nsetp.ne.u32 p, %5, 0;\n@p red.global.add.v4.f32 [%0], {%1,%2,%3,%4};\n}" ::"l"(gp + i * 512), "f"(prev[4 * i]),
                     "f"(prev[4 * i + 1]), "f"(prev[4 * i + 2]), "f"(prev[4 * i + 3]), "r"(on) : "memory");
      };
      constexpr int NE = 8;
#pragma unroll
      for (int i = (16 * e) / NE; i < (16 * (e + 1)) / NE; i++) red(i, (uint32_t)do_epi);
    }
    if (!DRAINED || j > 0) {
      wg_wait<1>();
      if (j > 0 || do_epi) nb_arrive(NB_WE + (j + NW - 1) % NW, 160);
    }
    if (j < 11) asm volatile("{\n.reg .pred p;\nsetp.lt.s32 p, %0, %1;\n@p wgmma.wait_group.sync.aligned 0;\n}" ::"r"(prog), "r"(target + j / 4) : "memory");
    if (!DRAINED && j == 0) pin(prev);
    if (GELU && e == 9) {
      if (sig == 7) nb_arrive(NB_H6, 160);
      if (sig >= 8) {
        asm volatile("fence.proxy.async.shared::cta;" ::: "memory");
        __syncwarp();
        if (st.lead) mbar_arrive(bar + (sig == 8 ? B_H7 : B_H8) * 8);
      }
    }
    if (!GELU && RES && e == 7 && sig == 8) { __syncwarp(); if (st.lead) mbar_arrive(bar + B_RED * 8); }
    if (RES) {
      if (j > 0 && (3 * j) / 4 > (3 * (j - 1)) / 4 && sig == 8 && st.lead) mbar_arrive(bar + (B_RESE + (3 * j) / 4 - 1) * 8);
    }
  }
}
__device__ __forceinline__ void gemm_drain(float (&cur)[64]) {
  wg_wait<0>();
  pin(cur);
  nb_arrive(NB_WE + NW - 1, 160);
}

__device__ __forceinline__ uint32_t exp2_pair_fix(float t0, float t1, uint32_t kc) {
  uint32_t z = __byte_perm(__float_as_uint(t0), __float_as_uint(t1), 0x6521);
  uint32_t mh;
  asm("lop3.b32 %0, %1, 0x007F007F, %2, 0xEA;" : "=r"(mh) : "r"(z), "r"(kc));
  uint32_t e = z - mh;
  uint32_t r;
  asm("fma.rn.bf16x2 %0, %1, %2, %3;" : "=r"(r) : "r"(z), "r"(mh), "r"(e));
  return r;
}
__device__ __forceinline__ void softmax_tile(const float (&s)[32], uint32_t (&p)[16], uint32_t kc) {
#pragma unroll
  for (int i = 0; i < 8; i++) {
    if ((POLY_MASK >> i) & 1) {
      p[2 * i + 0] = exp2_pair_fix(s[4 * i + 0], s[4 * i + 1], kc);
      p[2 * i + 1] = exp2_pair_fix(s[4 * i + 2], s[4 * i + 3], kc);
    } else {
      p[2 * i + 0] = pack_bf16(ex2f(s[4 * i + 0]), ex2f(s[4 * i + 1]));
      p[2 * i + 1] = pack_bf16(ex2f(s[4 * i + 2]), ex2f(s[4 * i + 3]));
    }
  }
}

__device__ __forceinline__ unsigned max_sqnorm(const uint8_t* p, const uint8_t* px, int lane) {
  auto H = [](uint32_t v) { return *reinterpret_cast<__nv_bfloat162*>(&v); };
  const int o = (lane & 15) * 128 + (lane >> 4) * 16;
  uint4 v = __ldcg((const uint4*)(px + o));
  __nv_bfloat162 s0 = __hmul2(H(v.x), H(v.x)), s1 = __hmul2(H(v.y), H(v.y)), s2 = __hmul2(H(v.z), H(v.z)), s3 = __hmul2(H(v.w), H(v.w));
#pragma unroll 2
  for (int i = 0; i < 8; i++) {
    v = __ldcg((const uint4*)(p + (i >> 2) * 2048 + (i & 3) * 32 + o));
    s0 = __hfma2(H(v.x), H(v.x), s0); s1 = __hfma2(H(v.y), H(v.y), s1); s2 = __hfma2(H(v.z), H(v.z), s2); s3 = __hfma2(H(v.w), H(v.w), s3);
  }
  s0 = __hadd2(s0, __shfl_xor_sync(~0u, s0, 16)); s1 = __hadd2(s1, __shfl_xor_sync(~0u, s1, 16));
  s2 = __hadd2(s2, __shfl_xor_sync(~0u, s2, 16)); s3 = __hadd2(s3, __shfl_xor_sync(~0u, s3, 16));
  s0 = __hmax2_nan(__hmax2_nan(s0, s1), __hmax2_nan(s2, s3));
  return __reduce_max_sync(~0u, __float_as_uint(__bfloat162float(__hmax_nan(s0.x, s0.y))) & 0x7FFFFFFFu);
}
__device__ __forceinline__ void mma16816(float* d, uint32_t a0, uint32_t a1, uint32_t a2, uint32_t a3, uint32_t b0, uint32_t b1) {
  asm volatile("mma.sync.aligned.m16n8k16.row.col.f32.bf16.bf16.f32 {%0,%1,%2,%3}, {%4,%5,%6,%7}, {%8,%9}, {%0,%1,%2,%3};"
               : "+f"(d[0]), "+f"(d[1]), "+f"(d[2]), "+f"(d[3]) : "r"(a0), "r"(a1), "r"(a2), "r"(a3), "r"(b0), "r"(b1));
}
__device__ __forceinline__ void attn_safe(float (&o)[12], const uint8_t* kv, uint32_t q0, uint32_t q1, uint32_t q2, uint32_t q3, uint32_t q4, uint32_t q5) {
  float m0 = -INFINITY, m1 = -INFINITY;
#pragma unroll
  for (int i = 0; i < 12; i++) o[i] = 0.f;
#pragma unroll 1
  for (int kt = 0; kt < S_ / 16; kt++) {
    const uint8_t* p = kv + (size_t)(kt >> 3) * KVB + (kt & 7) * 256;
    uint32_t f[5][2];
#pragma unroll
    for (int pl = 0; pl < 5; pl++) { f[pl][0] = __ldcg((const uint32_t*)(p + pl * 2048)); f[pl][1] = __ldcg((const uint32_t*)(p + pl * 2048 + 128)); }
    float s[2][4];
#pragma unroll
    for (int n = 0; n < 2; n++) {
      s[n][0] = s[n][1] = s[n][2] = s[n][3] = 0.f;
      mma16816(s[n], q0, q1, q2, q3, movm(f[0][n]), movm(f[1][n]));
      mma16816(s[n], q4, q5, 0u, 0u, movm(f[4][n]), 0u);
    }
    float n0 = fmaxf(fmaxf(s[0][0], s[0][1]), fmaxf(s[1][0], s[1][1])), n1 = fmaxf(fmaxf(s[0][2], s[0][3]), fmaxf(s[1][2], s[1][3]));
#pragma unroll
    for (int d = 1; d <= 2; d <<= 1) { n0 = fmaxf(n0, __shfl_xor_sync(~0u, n0, d)); n1 = fmaxf(n1, __shfl_xor_sync(~0u, n1, d)); }
    n0 = fmaxf(n0, m0); n1 = fmaxf(n1, m1);
    const float c0 = ex2f(m0 - n0), c1 = ex2f(m1 - n1);
    m0 = n0; m1 = n1;
#pragma unroll
    for (int i = 0; i < 12; i++) o[i] *= (i & 2) ? c1 : c0;
    const uint32_t p0 = pack_bf16(ex2f(s[0][0] - m0), ex2f(s[0][1] - m0)), p1 = pack_bf16(ex2f(s[0][2] - m1), ex2f(s[0][3] - m1));
    const uint32_t p2 = pack_bf16(ex2f(s[1][0] - m0), ex2f(s[1][1] - m0)), p3 = pack_bf16(ex2f(s[1][2] - m1), ex2f(s[1][3] - m1));
#pragma unroll
    for (int n = 0; n < 3; n++) mma16816(o + 4 * n, p0, p1, p2, p3, f[2 + n][0], f[2 + n][1]);
  }
}

#define TMA2D(...) tma2d_h(__VA_ARGS__, pol)
#define BULKLD(...) bulk_ld_h(__VA_ARGS__, pol)
__global__ void __launch_bounds__(512, 1)
main_kernel(const __grid_constant__ CUtensorMap tm_x, const __grid_constant__ CUtensorMap tm_wqkv,
            const __grid_constant__ CUtensorMap tm_w1, const __grid_constant__ CUtensorMap tm_w2,
            const __grid_constant__ CUtensorMap tm_wo, const __grid_constant__ CUtensorMap tm_out,
            const __grid_constant__ Descs ds, const bf16* __restrict__ x, const bf16* __restrict__ b1,
            const bf16* __restrict__ b2, bf16* __restrict__ out, const uint8_t* __restrict__ wqkv,
            const uint8_t* __restrict__ w1, const uint8_t* __restrict__ w2, const uint8_t* __restrict__ wo) {
  extern __shared__ __align__(1024) uint8_t smem[];
  if (smem_u32(smem) != SB0) __trap();
  constexpr uint32_t sb = SB0;
  constexpr uint32_t bar = sb + SM_BAR;
#define ROT 0
  const int tid = (ROT == 0) ? threadIdx.x : (ROT == 1) ? ((threadIdx.x + 256) & 511) : (ROT == 2) ? (511 - 127 - (threadIdx.x & ~127) + (threadIdx.x & 127)) :
                  ((threadIdx.x < 128) ? threadIdx.x + 256 : (threadIdx.x < 384 ? threadIdx.x - 128 : threadIdx.x));
  const int lane = tid & 31;
  const int warp = __shfl_sync(0xffffffffu, tid >> 5, 0);
  const bool spare = blockIdx.x >= NRT * NG;
  const int r = spare ? (blockIdx.x - NRT * NG) * 4 : blockIdx.x >> 3, g = blockIdx.x & 7;
  const int nq = spare ? 12 : 3;
  auto job_chunk = [&](int ch) { return qkv_chunk(spare ? 24 + ch % 3 : g + 8 * ch); };
  TSC(tid == 0, 0); TSG(tid == 0, 62);

  uint32_t xv[2][9], xt[18];
  if (warp < 8 && !spare) {
    const uint32_t* xr = (const uint32_t*)(x + (size_t)(r * 128 + g * 16 + warp * 2) * D_);
#pragma unroll
    for (int j = 0; j < 18; j++) xv[j / 9][j % 9] = __ldg(xr + j * 32 + lane);
    const uint32_t* xp = (const uint32_t*)(x + (size_t)(r * 128 + (2 * g + (warp & 1)) * 8 + (lane >> 2)) * D_ + (warp >> 1) * 16) + (lane & 3);
#pragma unroll
    for (int c = 0; c < 18; c++) xt[c] = __ldg(xp + (c >> 1) * 32 + (c & 1) * 4);
  }
  if (warp == 13 || warp == 12) {
    const bool el0 = elect_one();
    if (el0) {
      if (warp == 13) {
#pragma unroll
        for (int kb = 0; kb < 9; kb++) mbar_init(bar + (B_X + kb) * 8, 1);
      } else {
#pragma unroll
        for (int s = 0; s < 6; s++) mbar_init(bar + (B_BF + s) * 8, 1);
      }
      asm volatile("fence.mbarrier_init.release.cluster;" ::: "memory");
    }
    __syncwarp();
    nb_arrive(0, 512);
    if (el0) {
      if (warp == 13) {
#pragma unroll
        for (int kb = 0; kb < 9; kb++) {
          mbar_expect(bar + (B_X + kb) * 8, 16384);
          tma2d(sb + kb * XP, &tm_x, kb * 64, r * 128, bar + (B_X + kb) * 8);
        }
      } else {
        const int c0 = job_chunk(0) * 64;
#pragma unroll
        for (int s = 0; s < 6; s++) {
          mbar_expect(bar + (B_BF + s) * 8, BST);
          tma2d(sb + SM_BIG + (5 - s) * BST, &tm_wqkv, c0, s * 96, bar + (B_BF + s) * 8);
        }
      }
    }
    __syncwarp();
    nb_sync(15, 512);
  } else {
    if (warp < 12) {
      if (elect_one()) {
#pragma unroll
        for (int k = 0; k < (B_X + 11) / 12; k++) {
          const int i = warp + 12 * k;
          if (i < B_X) mbar_init(bar + i * 8, (i < B_O || i == B_H8 || i == B_OF + 7 || i == B_OF + 8) ? 4 : (i < B_RESF ? 8 : (i == B_TAB ? 12 : 1)));
        }
        asm volatile("fence.mbarrier_init.release.cluster;" ::: "memory");
      }
    } else {
      if (tid == 448) sts32(sb + SM_TMP + 32, 1000);
#pragma unroll
      for (int kb = 0; kb < 9; kb++) *(uint4*)(smem + kb * XP + 16384 + (tid - 448) * 16) = make_uint4(0x3F803F80u, 0x3F803F80u, 0x3F803F80u, 0x3F803F80u);
      asm volatile("fence.proxy.async.shared::cta;" ::: "memory");
    }
    __syncwarp();
    nb_arrive(15, 512);
    nb_sync(0, 512);
    if (warp < 8 && !spare) {
      float mu[2], sq[2];
#pragma unroll
      for (int k = 0; k < 2; k++) {
        mu[k] = 0.f;
#pragma unroll
        for (int j = 0; j < 9; j++) mu[k] += bf_lo(xv[k][j]) + bf_hi(xv[k][j]);
      }
#pragma unroll
      for (int o = 16; o; o >>= 1) { mu[0] += __shfl_xor_sync(~0u, mu[0], o); mu[1] += __shfl_xor_sync(~0u, mu[1], o); }
#pragma unroll
      for (int k = 0; k < 2; k++) {
        mu[k] *= (1.0f / D_);
        sq[k] = 0.f;
#pragma unroll
        for (int j = 0; j < 9; j++) { float a = bf_lo(xv[k][j]) - mu[k], b = bf_hi(xv[k][j]) - mu[k]; sq[k] = fmaf(a, a, fmaf(b, b, sq[k])); }
      }
#pragma unroll
      for (int o = 16; o; o >>= 1) { sq[0] += __shfl_xor_sync(~0u, sq[0], o); sq[1] += __shfl_xor_sync(~0u, sq[1], o); }
#pragma unroll
      for (int k = 0; k < 2; k++) {
        const float var = sq[k] * (1.0f / D_);
        const float rs1 = fmaxf(rsqrtf(var + 1e-5f), 1e-37f);
        const float sc = rs1 * rsqrtf(fmaf(var * rs1, rs1, 1e-5f));
        if (lane == 0) {
          asm volatile("st.relaxed.gpu.global.v2.f32 [%0], {%1,%2};" ::"l"(g_st + r * 128 + g * 16 + warp * 2 + k), "f"(mu[k]), "f"(rs1) : "memory");
          *(float2*)(smem + SM_TMP + 64 + (warp * 2 + k) * 8) = make_float2(sc, mu[k]);
        }
      }
      nb_sync(NB_KVE, 256);
    {
      const float4 sn = *(const float4*)(smem + SM_TMP + 64 + ((warp & 1) * 8 + 2 * (lane & 3)) * 8);
      uint8_t* yp = g_y + (size_t)r * 147456 + (warp >> 1) * 4096 + (2 * g + (warp & 1)) * 128 + lane * 4;
#pragma unroll
      for (int c = 0; c < 18; c++) {
        const uint32_t v = movm(xt[c]);
        stg32(yp + (c >> 1) * 16384 + (c & 1) * 2048, pack_bf16((bf_lo(v) - sn.y) * sn.x, (bf_hi(v) - sn.w) * sn.z));
      }
      uint4* sp = (uint4*)(g_o + (size_t)r * 147456 + 54 * 2048 + g * 4608) + tid;
      sp[0] = make_uint4(~0u, ~0u, ~0u, ~0u);
      if (tid < 32) sp[256] = make_uint4(~0u, ~0u, ~0u, ~0u);
      __syncwarp();
      if (lane == 0) mbar_arrive(bar + B_LN * 8);
      TSC(tid == 32, 3);
    }
    }
  }

  if (warp < 12) {
    const int c3 = (warp >> 2) == 2 ? 0 : (warp >> 2) + 1;
    const int w = warp & 3, gq = lane >> 2, t = lane & 3;
    float qa[68];
#pragma unroll
    for (int i = 0; i < 68; i++) asm volatile("" : "=f"(qa[i]));
#pragma unroll 1
    for (int ch = c3; ch < nq; ch += 3) {
      const int tl = ch / 3;
      const uint64_t z = (uint64_t)(uint32_t)(ch >> 8);
      const uint64_t da = ds.w + z, db = ds.x + z;
      if (ch > 0) nb_sync(NB_KVE + 1 + c3, 256);
#pragma unroll
      for (int j = 0; j < 6; j++) {
        const int b0 = (j == 0) ? 0 : (6 * j - 1) / 4 + 1, b1 = (6 * j + 5) / 4;
#pragma unroll
        for (int b = b0; b <= b1; b++) mbar_wait_unless((uint32_t)c3, bar + (B_X + b) * 8, tl & 1);
        mbar_wait(bar + (B_BF + j) * 8, ch & 1);
        wg_fence();
#pragma unroll
        for (int u = 0; u < 6; u++) {
          const int ks = 6 * j + u;
          wgmma_ss136_tn(qa, da + ((SM_BIG + (5 - j) * BST) / 16 + u * 128), db + ((ks >> 2) * (XP / 16) + (ks & 3) * 2), ks != 0);
        }
        wg_commit();
        if (j == 5 && ch + 1 < nq) nb_arrive(NB_KVE + 1 + (c3 == 2 ? 0 : c3 + 1), 256);
        if (j > 0) {
          wg_wait<1>();
          nb_arrive(NB_WE + j - 1, 160);
          if (c3 == 2 && lane == 0) {
#pragma unroll
            for (int b = (6 * (j - 1)) / 4; b < (6 * j) / 4; b++) mbar_arrive(bar + (B_RAW + b) * 8);
          }
        }
      }
      const int cq = job_chunk(ch);
      const int part = cq / 9;
      uint8_t* pp[2];
#pragma unroll
      for (int hf = 0; hf < 2; hf++) {
        const int jj = (cq - part * 9) * 64 + w * 16 + hf * 8 + gq;
        const int head = jj / 18, dim = jj - head * 18;
        const bool toq = part == 0 && dim < 16;
        const int off = (dim < 16) ? ((part == 2 ? 2 : 0) + (dim >> 3)) * 2048 + (dim & 7) * 16 : 4 * 2048 + ((part == 0 ? 6 : (part - 1) * 2) + dim - 16) * 16;
        pp[hf] = (toq ? g_q : g_kv) + (size_t)(head * NRT + r + tl) * (toq ? QB : KVB) + off + t * 4;
      }
      const float qs = (part == 0) ? (0.23570226039551584f * 1.4426950408889634f) : 1.0f;
      mbar_wait(bar + B_STAT * 8, tl & 1);
      float4 sv[8];
#pragma unroll
      for (int i = 0; i < 8; i++) { sv[i] = *(const float4*)(smem + SM_S2 + t * 16 + i * 64); sv[i].y *= qs; sv[i].w *= qs; }
      wg_wait<0>();
      pin(qa);
      nb_arrive(NB_WE + 5, 160);
      if (c3 == 2 && lane == 0) { mbar_arrive(bar + (B_RAW + 7) * 8); mbar_arrive(bar + (B_RAW + 8) * 8); }
      TSC((tid & 127) == 0 && ch < 3, 8 + ch);
      const float c0 = -qa[64], c1 = -qa[66];
#pragma unroll
      for (int hh = 0; hh < 2; hh++) {
        if (hh) {
#pragma unroll
          for (int i = 0; i < 8; i++) { sv[i] = *(const float4*)(smem + SM_S2 + t * 16 + (8 + i) * 64); sv[i].y *= qs; sv[i].w *= qs; }
        }
#pragma unroll
        for (int k = 0; k < 8; k++) {
          const int i = hh * 8 + k;
          stg32(pp[0] + i * 128, pack_bf16(fmaf(sv[k].x, c0, qa[4 * i]) * sv[k].y, fmaf(sv[k].z, c0, qa[4 * i + 1]) * sv[k].w));
          stg32(pp[1] + i * 128, pack_bf16(fmaf(sv[k].x, c1, qa[4 * i + 2]) * sv[k].y, fmaf(sv[k].z, c1, qa[4 * i + 3]) * sv[k].w));
        }
      }
      if (spare) nb_sync(NB_EPI + c3, 160); else nb_arrive(NB_EPI + c3, 160);
      __syncwarp();
      if (lane == 0) mbar_arrive(bar + B_TAB * 8);
    }
  }

  if (warp >= 12) {
    asm volatile("setmaxnreg.dec.sync.aligned.u32 %0;" ::"n"(RG_P));
    const bool el = elect_one();
    const uint64_t pol = policy_evict_first();
    auto finish = [&]() {
      if (atomicAdd(&g_flags.done.v, 1u) == NRT * NG - 1) {
        Flag* f = (Flag*)&g_flags;
        for (int i = 0; i < (int)(sizeof(Flags) / sizeof(Flag)); i++) f[i].v = 0u;
        g_epoch = *(volatile unsigned*)&g_epoch + 1u;
      }
    };
    if (warp == 12) {
#pragma unroll 1
      for (int ch = 1; ch < nq; ch++) {
        const int c0 = job_chunk(ch) * 64;
#pragma unroll
        for (int s = 0; s < 6; s++) {
          nb_sync(NB_WE + s, 160);
          if (el) {
            mbar_expect(bar + (B_BF + s) * 8, BST);
            TMA2D(sb + SM_BIG + (5 - s) * BST, &tm_wqkv, c0, s * 96, bar + (B_BF + s) * 8);
          }
        }
      }
      if (!spare) {
#pragma unroll
        for (int s = 0; s < 6; s++) {
          nb_sync(NB_WE + s, 160);
          if (el) {
#pragma unroll
            for (int k = 0; k < NW; k++)
              if ((k + 1) / 2 == s) {
                mbar_expect(bar + (B_WF + k) * 8, WST);
                TMA2D(sb + SM_W + (NW - 1 - k) * WST, &tm_w1, g * 576, k * 48, bar + (B_WF + k) * 8);
              }
          }
        }
        if (el) mbar_arrive(bar + B_BIG * 8);
        auto half = [&](const CUtensorMap* tm, int c0, int k0) {
#pragma unroll
          for (int s = 0; s < NW; s++) {
            nb_sync(NB_WE + s, 160);
            if (el) {
              mbar_expect(bar + (B_WF + s) * 8, WST);
              TMA2D(sb + SM_W + (NW - 1 - s) * WST, tm, c0, k0 + s * 48, bar + (B_WF + s) * 8);
            }
          }
        };
        auto pf = [&](const CUtensorMap* tm, int c0, int k0) {
          if (r < 12 && el) asm volatile("cp.async.bulk.prefetch.tensor.2d.L2.global [%0, {%1, %2}];" ::"l"(tm), "r"(c0), "r"(k0 + r * 48) : "memory");
        };
        int c = (g + 1) * 64, cp = c;
        half(&tm_w1, g * 576, 288);
#pragma unroll 1
        for (int ch = 1; ch < 9; ch++) {
          if (ch < 7) pf(&tm_w1, g * 576 + (ch + 2) * 64, 0);
          else { pf(&tm_w2, cp, g * 576); cp += 64; if (cp == 576) cp = 0; }
          half(&tm_w1, g * 576 + ch * 64, 0);
          half(&tm_w1, g * 576 + ch * 64, 288);
        }
#pragma unroll 1
        for (int ch = 0; ch < 9; ch++) {
          if (ch < 7) { pf(&tm_w2, cp, g * 576); cp += 64; if (cp == 576) cp = 0; }
          half(&tm_w2, c, g * 576);
          half(&tm_w2, c, g * 576 + 288);
          c += 64; if (c == 576) c = 0;
        }
#pragma unroll 1
        for (int hc = 0; hc < 2; hc++) half(&tm_wo, g * 64, hc * 288);
      }
#pragma unroll
      for (int s = 0; s < NW; s++) nb_sync(NB_WE + s, 160);
    } else if (warp == 13) {
      if (spare) {
        if (el)
          for (int tl = 1; tl < 4; tl++)
            for (int kb = 0; kb < 9; kb++) {
              mbar_wait_slow(bar + (B_RAW + kb) * 8, (tl - 1) & 1);
              mbar_expect(bar + (B_X + kb) * 8, 16384);
              TMA2D(sb + kb * XP, &tm_x, kb * 64, (r + tl) * 128, bar + (B_X + kb) * 8);
            }
      } else {
        const unsigned tag = *(volatile unsigned*)&g_epoch + 1u;
        auto open_round = [&](int j) {
          const int h = g + 8 * j;
          const int c_lo = (h * 18) >> 6, c_hi = (h * 18 + 17) >> 6;
          if (lane < 7) flag_wait(&g_flags.qkv[lane == 6 ? 27 + g / 2 : (lane >> 1) * 9 + ((lane & 1) ? c_hi : c_lo)], lane == 6 ? 2 * NRT : NRT);
          __syncwarp();
          if (j == 0) mbar_wait_slow(bar + B_BIG * 8, 0);
          if (el) {
            asm volatile("fence.proxy.async.global;" ::: "memory");
            mbar_expect(bar + (B_QR + j) * 8, QB);
            BULKLD(sb + SM_Q, g_q + (size_t)(h * NRT + r) * QB, QB, bar + (B_QR + j) * 8);
          }
        };
        open_round(0);
        for (int j = 0; j < 4; j++) {
          const int h = g + 8 * j;
          const uint8_t* src = g_kv + (size_t)h * NRT * KVB;
          int kb = r;
#pragma unroll 1
          for (int t4 = 0; t4 < NRT / NKV; t4++) {
            if (t4 == 2 && j < 3) open_round(j + 1);
            if (t4 == 3) {
              uint2 v;
              int it = 0;
              do {
                asm volatile("ld.relaxed.gpu.global.v2.u32 {%0,%1}, [%2];" : "=r"(v.x), "=r"(v.y) : "l"(g_kn + h * 32 + (lane < 16 ? lane : 16 + r)) : "memory");
                if (++it > 4000000) __trap();
              } while (!__all_sync(~0u, v.y == tag));
              const float kn = __uint_as_float(__reduce_max_sync(~0u, lane < 16 ? v.x : 0u)), qn = __uint_as_float(__shfl_sync(~0u, v.x, 16));
              if (el) sts32(sb + SM_TMP + j * 4, (qn * kn <= 3200.f) ? 1u : 0u);
            }
#pragma unroll
            for (int s = 0; s < NKV; s++) {
              if (j > 0 || t4 > 0) nb_sync(NB_KVE + s, 288);
              if (el) {
                mbar_expect(bar + (B_KVF + s) * 8, KVB);
                BULKLD(sb + SM_KV + s * KVB, src + kb * KVB, KVB, bar + (B_KVF + s) * 8);
                sts32(sb + SM_TMP + 32, j * 16 + t4 * 4 + s);
                TSC(j == 0 && t4 == 0 && s == 0, 49);
              }
              kb = (kb + 1) & (NRT - 1);
            }
          }
        }
        for (int s = 0; s < NKV; s++) { nb_sync(NB_KVE + s, 288); if (el) sts32(sb + SM_TMP + 32, s < 2 ? 64 + s : 1000); }
        if (el) {
          mbar_expect(bar + B_XR * 8, 16384);
          TMA2D(sb + SM_XR, &tm_x, g * 64, r * 128, bar + B_XR * 8);
        }
#pragma unroll 1
        for (int t = 0; t < 12; t++) {
          const int s = t & (NKV - 1);
          if (t >= NKV) nb_sync(NB_KVE + s, 160);
          if (el) {
            mbar_expect(bar + (B_KVF + s) * 8, WST);
            TMA2D(sb + SM_KV + s * WST, &tm_wo, 512, t * 48, bar + (B_KVF + s) * 8);
          }
        }
      }
    } else if (warp == 14) {
      for (int tl = 0; tl < (spare ? 4 : 1); tl++) {
        float2 sv[4];
        int it = 0;
        bool ok;
        do {
          ok = true;
#pragma unroll
          for (int i = 0; i < 4; i++) {
            asm volatile("ld.relaxed.gpu.global.v2.f32 {%0,%1}, [%2];" : "=f"(sv[i].x), "=f"(sv[i].y) : "l"(g_st + (r + tl) * 128 + i * 32 + lane) : "memory");
            ok = ok && (sv[i].y != 0.f);
          }
          if (++it > 2000000) __trap();
        } while (!__all_sync(~0u, ok));
        if (tl > 0) mbar_wait_slow(bar + B_TAB * 8, (tl - 1) & 1);
#pragma unroll
        for (int i = 0; i < 4; i++) *(float2*)(smem + SM_S2 + (i * 32 + lane) * 8) = sv[i];
        __syncwarp();
        if (el) { mbar_arrive(bar + B_STAT * 8); TSC(1, 2); }
      }
      if (!spare) {
        if (el) {
          mbar_wait_slow(bar + B_LN * 8, 0);
          flag_add(&g_flags.ln[r]);
          if (r < 12)
            for (int c = 0; c < 3; c++)
              asm volatile("cp.async.bulk.prefetch.tensor.2d.L2.global [%0, {%1, %2}];" ::"l"(&tm_w1), "r"(g * 576 + c * 64), "r"(r * 48) : "memory");
          TSC(1, 44);
          flag_wait(&g_flags.ln[r], NG);
          fence_async_all();
          TSC(1, 45);
          for (int kb = 0; kb < 9; kb++) {
            mbar_wait_slow(bar + (B_RAW + kb) * 8, 0);
            mbar_expect(bar + (B_Y + kb) * 8, 16384);
            BULKLD(sb + SM_RES + kb * 16384, g_y + (size_t)r * 147456 + kb * 16384, 16384, bar + (B_Y + kb) * 8);
          }
          mbar_wait_slow(bar + B_TAB * 8, 0);
          mbar_expect(bar + B_BIAS * 8, 1152);
          bulk_ld(sb + SM_B1, b1 + g * 576, 1152, bar + B_BIAS * 8);

        }
        __syncwarp();
        nb_sync(NB_H6, 160);
        if (el) {
          flag_wait(&g_flags.ocnt[r * 4 + ZROUND], NG);
          const uint8_t* src = g_h + (size_t)(r * 72 + g * 9) * 16384;
          asm volatile("fence.acq_rel.gpu;" ::: "memory"); fence_async_all();
          for (int kb = 0; kb < 8; kb++) {
            mbar_wait_slow(bar + (B_RESE + kb) * 8, 0);
            if (kb == 7) { mbar_wait_slow(bar + B_H7 * 8, 0); asm volatile("fence.acq_rel.gpu;" ::: "memory"); fence_async_all(); }
            mbar_expect(bar + (B_RESF + kb) * 8, 16384);
            BULKLD(sb + SM_RES + kb * 16384, src + (size_t)kb * 16384, 16384, bar + (B_RESF + kb) * 8);
          }
          flag_wait_sleep(&g_flags.ocnt[r * 4 + 1], NG);
          flag_wait_sleep(&g_flags.ocnt[r * 4 + 2], NG);
          fence_async_all();
          l2_prefetch(x + (size_t)(r * 128 + g * 16) * D_, 16 * D_ * 2);
          l2_prefetch(wo + blockIdx.x * 5184, 5184);
          mbar_wait_sleep(bar + B_RESE * 8, 1);
          for (int kb = 0; kb < 7; kb++) {
            const uint32_t bytes = kb < 6 ? 16384 : 12288;
            mbar_wait_slow(bar + (B_RESE + kb) * 8, 1);
            mbar_expect(bar + (B_OF + kb) * 8, bytes);
            BULKLD(sb + SM_RES + kb * 16384, g_o + (size_t)r * 147456 + kb * 16384, bytes, bar + (B_OF + kb) * 8);
          }
          mbar_wait_slow(bar + (B_OF + 8) * 8, 0);
          mbar_wait_slow(bar + B_ACC * 8, 0);
          for (int i = 0; i < 8; i++) *(float4*)(g_st + r * 128 + g * 16 + i * 2) = make_float4(0.f, 0.f, 0.f, 0.f);
          finish();
        }
      }
    } else {
      if (!spare) {
        if (el && r < 12)
          asm volatile("cp.async.bulk.prefetch.tensor.2d.L2.global [%0, {%1, %2}];" ::"l"(&tm_wqkv), "r"(job_chunk(1 + r / 6) * 64), "r"((r % 6) * 96) : "memory");
#pragma unroll 1
        for (int i = lane; i < 128; i += 32) {
          const int j = i >> 5, grp = (i >> 1) & 15, rw = i & 1;
          uint32_t v = rw ? 0x3F80u : (((POLY_MASK >> (grp & 7)) & 1) ? MAGIC_P : MAGIC_M);
          v |= v << 16;
          *(uint4*)(g_kv + (size_t)((g + 8 * j) * NRT + r) * KVB + 4 * 2048 + grp * 128 + 64 + rw * 16) = make_uint4(v, v, v, v);
        }
        __syncwarp();
        if (el) flag_add(&g_flags.qkv[27 + g / 2]);
      }
      for (int ch = 0; ch < nq; ch++) {
        __syncwarp();
        nb_sync(NB_EPI + ch % 3, 160);
        if (el) flag_add(&g_flags.qkv[job_chunk(ch)]);
        TSC(el && ch < 2, 52 + ch);
      }
      if (!spare) {
        const unsigned tag = *(volatile unsigned*)&g_epoch + 1u;
        auto norms = [&](int j) {
          const int h = g + 8 * j;
          mbar_wait_sleep(bar + (B_QR + j) * 8, 0);
          const uint8_t* kp = g_kv + (size_t)(h * NRT + r) * KVB;
          const unsigned kn = max_sqnorm(kp, kp + 8192, lane), qn = max_sqnorm(g_q + (size_t)(h * NRT + r) * QB, kp + 8192 + 96, lane);
          if (lane < 2) asm volatile("st.relaxed.gpu.global.v2.u32 [%0], {%1,%2};" ::"l"(g_kn + h * 32 + lane * 16 + r), "r"(lane ? qn : kn), "r"(tag) : "memory");
        };
        norms(0);
        for (int j = 0; j < 3; j++) {
          norms(j + 1);
          mbar_wait_sleep(bar + (B_O + j) * 8, 0);
          if (j == ZROUND) {
            float4* zp = (float4*)(g_acc + (size_t)r * 9 * 8192 + g * 9216) + lane;
#pragma unroll 1
            for (int i = 0; i < 12; i++) {
#pragma unroll
              for (int k = 0; k < 6; k++) zp[k * 32] = make_float4(0.f, 0.f, 0.f, 0.f);
              zp += 192;
              __nanosleep(400);
            }
            __syncwarp();
          }
          if (el) flag_add(&g_flags.ocnt[r * 4 + j]);
        }
      }
      if (el && !spare) {
        mbar_wait_slow(bar + B_RED * 8, 0);
        flag_add(&g_flags.red[r]);
        flag_wait(&g_flags.red[r], NG);
        mbar_arrive(bar + B_ACC * 8);
        TSC(1, 41);
      }
    }
  } else if (spare) {
  } else if (warp >= 8) {
    asm volatile("setmaxnreg.inc.sync.aligned.u32 %0;" ::"n"(RG_G));
    const int w = warp - 8, gq = lane >> 2, t = lane & 3;
    TSC(tid == 256, 5);
    GState st{lane == 0, 0u};
    {
      float d0[64], d1[64];
#pragma unroll
      for (int i = 0; i < 64; i++) asm volatile("" : "=f"(d0[i]), "=f"(d1[i]));
      auto nohook = []() {};
      const uint32_t oa = sb + SM_XR + ((lane & 7) + (lane >> 4) * 8) * 128 + (((2 * w + ((lane >> 3) & 1)) ^ (lane & 7)) << 4);
      auto sched = [&](int c) { return c <= 9 ? ds.sa + ((c * ds.sb) >> 4) : ds.sa + ((9 * ds.sb + (c - 9) * ds.sc) >> 4); };
      auto red_ptr = [&](int c2) {
        int c = c2 + g + 1; if (c >= 9) c -= 9;
        return (uint8_t*)(g_acc + (size_t)(r * 9 + c) * 8192 + w * 2048 + lane * 4);
      };
#pragma unroll 1
      for (int it = 0; it < 6; it++) {
        const bool mid = (it >= 1 && it <= 4);
        if (mid) gemm_chunk<false, true, false>(d1, d0, red_ptr(2 * it - 2), st, ds, it, true, false, 1u, 0u, sched(8 + 2 * it), nohook);
        gemm_chunk<false, false, true>(d0, d1, red_ptr(2 * it - 1), st, ds, 2 * it, mid, it == 5, (uint32_t)mid,
                                       bar + (it == 0 ? B_Y : B_OF) * 8, mid ? sched(9 + 2 * it) : 0, [&]() {
          if (it == 5) {
            asm volatile("prefetch.tensormap [%0];" ::"l"(&tm_out) : "memory");
            wg_wait<0>();
            pin(d0);
            mbar_wait(bar + B_ACC * 8, 0);
            const float4* ap = (const float4*)red_ptr(8);
#pragma unroll
            for (int i = 0; i < 16; i++) { const float4 q = __ldcg(ap + i * 32); d1[4 * i] = q.x; d1[4 * i + 1] = q.y; d1[4 * i + 2] = q.z; d1[4 * i + 3] = q.w; }
            const float c0 = __bfloat162float(b2[g * 64 + w * 16 + gq]), c1 = __bfloat162float(b2[g * 64 + w * 16 + gq + 8]);
            mbar_wait(bar + B_XR * 8, 0);
#pragma unroll
            for (int i = 0; i < 8; i++) {
              uint32_t v[4];
              asm volatile("ldmatrix.sync.aligned.m8n8.x4.trans.shared.b16 {%0,%1,%2,%3}, [%4];" : "=r"(v[0]), "=r"(v[1]), "=r"(v[2]), "=r"(v[3]) : "r"(oa + i * 2048) : "memory");
#pragma unroll
              for (int k = 0; k < 4; k++) { d0[8 * i + 2 * k] += bf_lo(v[k]) + ((k & 1) ? c1 : c0); d0[8 * i + 2 * k + 1] += bf_hi(v[k]) + ((k & 1) ? c1 : c0); }
            }
#pragma unroll
            for (int i = 0; i < 64; i++) d0[i] += d1[i];
            pin(d0);
          }
        });
        if (it == 5) break;
        gemm_drain(d0);
        if (it == 4 && st.lead) mbar_arrive(bar + (B_RESE + 8) * 8);
        TSC(tid == 256, it == 0 ? 11 : 17 + it);
        if (it == 0) {
          uint8_t* hp = g_h + (size_t)(r * 72 + g * 9) * 16384 + (2 * w) * 2048 + lane * 4;
          mbar_wait(bar + B_BIAS * 8, 0);
#pragma unroll 1
          for (int c = 1; c < 10; c++) {
            const bf16* bs = (const bf16*)(smem + SM_B1) + (c - 1) * 64 + w * 16 + gq;
            const float b0 = 0.5f * __bfloat162float(bs[0]), b1v = 0.5f * __bfloat162float(bs[8]);
#pragma unroll
            for (int i = 0; i < 64; i++) d1[i] = fmaf(d0[i], 0.5f, (i & 2) ? b1v : b0);
            pin(d1);
            if (c == 9) {
              nb_sync(NB_GEMM, 128);
              hp = smem + SM_RES + 8 * 16384 + (2 * w) * 2048 + lane * 4;
            }
            gemm_chunk<true, true, true>(d0, d1, hp, st, ds, c, true, false, (uint32_t)(c != 9), bar + B_RESF * 8, sched(c), nohook);
            hp += 16384;
            gemm_drain(d0);
            TSC(tid == 256 && (!(c & 1) || c == 9), 12 + ((c + 1) >> 1));
          }
        }
      }
      {
        gemm_drain(d0);
        TSC(tid == 256, 43);
#pragma unroll
        for (int i = 0; i < 8; i++)
          asm volatile("stmatrix.sync.aligned.m8n8.x4.trans.shared.b16 [%0], {%1,%2,%3,%4};" ::"r"(oa + i * 2048),
                       "r"(pack_bf16(d0[8 * i], d0[8 * i + 1])), "r"(pack_bf16(d0[8 * i + 2], d0[8 * i + 3])),
                       "r"(pack_bf16(d0[8 * i + 4], d0[8 * i + 5])), "r"(pack_bf16(d0[8 * i + 6], d0[8 * i + 7])) : "memory");
        asm volatile("fence.proxy.async.shared::cta;" ::: "memory");
        nb_sync(NB_GEMM, 128);
        if (warp == 8 && elect_one()) {
          asm volatile("cp.async.bulk.tensor.2d.global.shared::cta.bulk_group [%0, {%2, %3}], [%1];" ::"l"(&tm_out), "r"(sb + SM_XR), "r"(g * 64), "r"(r * 128) : "memory");
          asm volatile("cp.async.bulk.commit_group;\ncp.async.bulk.wait_group.read 0;" ::: "memory");
        }
      }
      TSC(tid == 256, 22); TSG(tid == 256, 63);
    }
  } else {
    asm volatile("setmaxnreg.inc.sync.aligned.u32 %0;" ::"n"(RG_A));
    const int gq = lane >> 2, t = lane & 3;
    uint32_t ph = 0;
    const uint32_t zr = (uint32_t)(ds.dbg >> 30), zr2 = (uint32_t)(ds.dbg >> 29), kc = 0x9F809F80u + zr;
#define SFENCE()
#define ISSUE_S(S, off) { wgmma_rs64_t_z(S, q0, q1, q2, q3, dk0 + (off)); wgmma_rs64_t(S, q4, q5, zr, zr2, dkx + (off)); }
#define ISSUE_PV(P, off) { _Pragma("unroll") for (int k = 0; k < 4; k++) wgmma_rs24_n(o, P[4 * k], P[4 * k + 1], P[4 * k + 2], P[4 * k + 3], dv + ((off) + k * 16)); }
    uint32_t q0, q1, q2, q3, q4, q5;
    const uint32_t ma = ((lane >> 4) & 1) * 2048 + (2 * warp + ((lane >> 3) & 1)) * 128;
    auto load_q = [&]() {
      asm volatile("ldmatrix.sync.aligned.m8n8.x4.trans.shared.b16 {%0,%1,%2,%3}, [%4];" : "=r"(q0), "=r"(q1), "=r"(q2), "=r"(q3) : "r"(sb + SM_Q + ma + (lane & 7) * 16) : "memory");
      asm volatile("ldmatrix.sync.aligned.m8n8.x2.trans.shared.b16 {%0,%1}, [%2];" : "=r"(q4), "=r"(q5) : "r"(sb + SM_KV + 8192 + (ma & 2047) + ((lane + 6) & 7) * 16) : "memory");
      if (t != 0) { q4 = (t == 2) ? 0x00003F80u : 0u; q5 = q4; }
    };
    float o[12], sa[32], sbb[32];
    uint32_t pa[16], pb[16];
    {
      const uint64_t dk0 = ds.k0, dkx = ds.kx;
      mbar_wait_nap(bar + B_QR * 8, 0);
      mbar_wait(bar + B_KVF * 8, 0);
      load_q();
      wg_fence();
      ISSUE_S(sa, 0);
      wg_commit();
    }
#pragma unroll 1
    for (int j = 0; j < 4; j++) {
      const int h = g + 8 * j;
      TSC((tid & 127) == 0, 24 + (tid >> 7) * 8 + 2 * j);
      wg_wait<0>();
#pragma unroll
      for (int i = 0; i < 12; i++) o[i] = 0.f;
      pin(o);
      TSC(tid == 0 && j == 0, 6);
      TSC(tid == 0, 54 + j);
#pragma unroll 1
      for (int s4 = 0; s4 < NRT / NKV; s4++) {
        const uint64_t z64 = (uint64_t)(uint32_t)(s4 >> 8);
        const uint64_t dk0 = ds.k0 + z64, dkx = ds.kx + z64, dv = ds.v + z64;
#pragma unroll
        for (int sl = 0; sl < NKV; sl++) {
          constexpr int SS = KVB / 16;
          const int nx = (sl + 1) % NKV;
          if (sl == NKV - 1) ph ^= 1;
          pin(sa);
          SFENCE();
          ISSUE_S(sbb, sl * SS + 64);
          wg_commit();
          uint32_t rdy = mbar_test(bar + (B_KVF + nx) * 8, ph);
          softmax_tile(sa, pa, kc);
          pin(pa);
          wg_fence();
          ISSUE_PV(pa, sl * SS);
          wg_commit();
          if (sl == NKV - 1) rdy |= (uint32_t)(s4 + 1 == NRT / NKV && j == 3);
          mbar_wait_unless(rdy, bar + (B_KVF + nx) * 8, ph);
          wg_wait<1>();
          pin(sbb);
          if (sl > 0 || s4 > 0) nb_arrive(NB_KVE + (sl + NKV - 1) % NKV, 288);
          if (sl == NKV - 1 && s4 + 1 == NRT / NKV && j < 3) {
            mbar_wait(bar + (B_QR + j + 1) * 8, 0);
            load_q();
          }
          wg_fence();
          ISSUE_S(sa, nx * SS);
          wg_commit();
          softmax_tile(sbb, pb, kc);
          pin(pb);
          wg_fence();
          ISSUE_PV(pb, sl * SS + 64);
          wg_commit();
          wg_wait<1>();
        }
      }
      wg_wait<0>();
      pin(o);
      nb_arrive(NB_KVE + NKV - 1, 288);
      TSC(tid == 0, 58 + j);
      float i0, i1;
      {
        const unsigned inrange = *(const volatile unsigned*)(smem + SM_TMP + j * 4);
        i0 = rcp_fast(__shfl_sync(~0u, o[9], (lane & ~3) + 2)); i1 = rcp_fast(__shfl_sync(~0u, o[11], (lane & ~3) + 2));
        float a0 = fmaxf(fmaxf(fabsf(o[0]), fabsf(o[1])), fmaxf(fabsf(o[4]), fabsf(o[5]))), a1 = fmaxf(fmaxf(fabsf(o[2]), fabsf(o[3])), fmaxf(fabsf(o[6]), fabsf(o[7])));
        float sum = (o[0] + o[1] + o[4] + o[5]) + (o[2] + o[3] + o[6] + o[7]);
        if (t == 1) sum += (o[8] + o[9]) + (o[10] + o[11]);
        const bool ok = inrange && (a0 * i0 >= 1e-12f) && (a1 * i1 >= 1e-12f) && (fabsf(sum) <= 3e38f) && !(ds.dbg & 1);
        if (!__all_sync(~0u, ok)) {
          const uint8_t* qp = g_q + (size_t)(h * NRT + r) * QB + (warp * 2) * 128 + lane * 4;
          const uint8_t* xp = g_kv + (size_t)(h * NRT + r) * KVB + 8192 + (warp * 2) * 128 + 96 + (lane & 7) * 4;
          const uint32_t f4 = movm(lane < 8 ? __ldcg((const uint32_t*)xp) : 0u), f5 = movm(lane < 8 ? __ldcg((const uint32_t*)(xp + 128)) : 0u);
          attn_safe(o, g_kv + (size_t)h * NRT * KVB + lane * 4, movm(__ldcg((const uint32_t*)qp)), movm(__ldcg((const uint32_t*)(qp + 128))),
                    movm(__ldcg((const uint32_t*)(qp + 2048))), movm(__ldcg((const uint32_t*)(qp + 2048 + 128))), f4, f5);
          i0 = rcp_fast(__shfl_sync(~0u, o[9], (lane & ~3) + 2)); i1 = rcp_fast(__shfl_sync(~0u, o[11], (lane & ~3) + 2));
        }
      }
      if (j == 3) mbar_wait(bar + B_Y * 8, 0);
      {
        uint8_t* ob = g_o + (size_t)r * 147456 + (warp * 2) * 128 + t * 4;
#pragma unroll
        for (int n = 0; n < 3; n++) {
          const uint32_t v0 = movm(pack_bf16(o[4 * n] * i0, o[4 * n + 1] * i0)), v1 = movm(pack_bf16(o[4 * n + 2] * i1, o[4 * n + 3] * i1));
          const int col = h * 18 + (n < 2 ? n * 8 + gq : 14 + gq);
          if (n < 2 || (gq >> 1) == 1) {
            stg32(ob + (col >> 3) * 2048 + (col & 7) * 16, v0);
            stg32(ob + (col >> 3) * 2048 + (col & 7) * 16 + 128, v1);
          }
        }
      }
      __syncwarp();
      if (lane == 0 && j < 3) mbar_arrive(bar + (B_O + j) * 8);
      TSC((tid & 127) == 0, 24 + (tid >> 7) * 8 + 2 * j + 1);
    }
    if (warp >= 4) {
      const uint4* src = (const uint4*)(g_o + (size_t)r * 147456 + 54 * 2048) + (tid - 128);
      uint4 v[18];
#pragma unroll
      for (int i = 0; i < 18; i++) asm volatile("" : "=r"(v[i].x), "=r"(v[i].y), "=r"(v[i].z), "=r"(v[i].w));
      uint32_t pend = 0x3FFFFu;
      int it = 0;
      do {
#pragma unroll
        for (int i = 0; i < 18; i++)
          asm volatile("{\n.reg .pred p;\nsetp.ne.u32 p, %5, 0;\n@p ld.relaxed.gpu.global.v4.u32 {%0,%1,%2,%3}, [%4];\n}"
                       : "+r"(v[i].x), "+r"(v[i].y), "+r"(v[i].z), "+r"(v[i].w) : "l"(src + i * 128), "r"(pend & (1u << i)) : "memory");
        pend = 0;
#pragma unroll
        for (int i = 0; i < 18; i++) pend |= (__vimax3_u32(__vimax3_u32(v[i].x, v[i].y, v[i].z), v[i].w, 0u) == ~0u) ? (1u << i) : 0u;
        if (!__any_sync(~0u, pend != 0)) break;
        __nanosleep(NAP);
      } while (++it < 4000000);
      TSC(tid == 128, 42);
      mbar_wait_nap(bar + (B_RESE + 8) * 8, 0);
#pragma unroll
      for (int i = 0; i < 18; i++) *(uint4*)(smem + SM_RES + 54 * 2048 + (i * 128 + tid - 128) * 16) = v[i];
      asm volatile("fence.proxy.async.shared::cta;" ::: "memory");
      __syncwarp();
      if (lane == 0) { mbar_arrive(bar + (B_OF + 7) * 8); mbar_arrive(bar + (B_OF + 8) * 8); }
    } else {
      float d2[8];
      const size_t eo = (size_t)(r * 128 + g * 16 + gq) * D_ + 512 + warp * 16 + t * 2;
#pragma unroll
      for (int i = 0; i < 4; i++) {
        const uint32_t v = movm(__ldg((const uint32_t*)(x + eo + (i >> 1) * (8 * D_) + (i & 1) * 8)));
        const float c = __bfloat162float(b2[512 + warp * 16 + gq + (i & 1) * 8]);
        d2[2 * i] = bf_lo(v) + c; d2[2 * i + 1] = bf_hi(v) + c;
      }
      pin(d2);
      float4 av[2];
#pragma unroll 1
      for (int j4 = 0; j4 < 3; j4++) {
        const uint64_t da = ds.w + (uint64_t)(SM_KV / 16), db = ds.h + (uint64_t)(uint32_t)(j4 * 3072 + g * 16);
        if (j4 == 2) {
          mbar_wait_nap(bar + B_ACC * 8, 0);
          const float4* ap2 = (const float4*)(g_acc + (size_t)(r * 9 + 8) * 8192 + warp * 2048 + (2 * g) * 128 + lane * 4);
          av[0] = __ldcg(ap2); av[1] = __ldcg(ap2 + 32);
        }
#pragma unroll
        for (int s = 0; s < 4; s++) {
          if (s < 3) mbar_wait_nap(bar + (B_OF + j4 * 3 + s) * 8, 0);
          mbar_wait(bar + (B_KVF + s) * 8, ph);
          wg_fence();
#pragma unroll
          for (int u = 0; u < 3; u++) wgmma_ss16_tt(d2, da + (s * (WST / 16) + u * 128), db + (3 * s + u) * 256, 1);
          wg_commit();
          wg_wait<0>();
          if (j4 < 2) nb_arrive(NB_KVE + s, 160);
        }
        ph ^= 1;
      }
      pin(d2);
      uint8_t* op2 = (uint8_t*)(out + eo);
#pragma unroll
      for (int i = 0; i < 2; i++) {
        stg32(op2 + i * (8 * D_ * 2), movm(pack_bf16(d2[4 * i] + av[i].x, d2[4 * i + 1] + av[i].y)));
        stg32(op2 + i * (8 * D_ * 2) + 16, movm(pack_bf16(d2[4 * i + 2] + av[i].z, d2[4 * i + 3] + av[i].w)));
      }
      TSC(tid == 0, 40);
    }
  }
}

typedef CUresult (*enc_fn)(CUtensorMap*, CUtensorMapDataType, cuuint32_t, void*, const cuuint64_t*, const cuuint64_t*,
                           const cuuint32_t*, const cuuint32_t*, CUtensorMapInterleave, CUtensorMapSwizzle,
                           CUtensorMapL2promotion, CUtensorMapFloatOOBfill);
static void make_map(enc_fn enc, CUtensorMap* tm, const void* p, int cols, int rows, int bc, int br) {
  cuuint64_t gd[2] = {(cuuint64_t)cols, (cuuint64_t)rows};
  cuuint64_t gs[1] = {(cuuint64_t)cols * 2};
  cuuint32_t bx[2] = {(cuuint32_t)bc, (cuuint32_t)br};
  cuuint32_t es[2] = {1, 1};
  enc(tm, CU_TENSOR_MAP_DATA_TYPE_BFLOAT16, 2, (void*)p, gd, gs, bx, es, CU_TENSOR_MAP_INTERLEAVE_NONE,
      CU_TENSOR_MAP_SWIZZLE_128B, CU_TENSOR_MAP_L2_PROMOTION_L2_256B, CU_TENSOR_MAP_FLOAT_OOB_FILL_NONE);
}

extern "C" void kernel_launch(void* const* d_in, const int* in_sizes, int n_in, void* d_out, int out_size) {
  const bf16* x = (const bf16*)d_in[0];
  const bf16* wqkv = (const bf16*)d_in[1];
  const bf16* wo = (const bf16*)d_in[2];
  const bf16* w1 = (const bf16*)d_in[4];
  const bf16* b1 = (const bf16*)d_in[5];
  const bf16* w2 = (const bf16*)d_in[6];
  const bf16* b2 = (const bf16*)d_in[7];
  static enc_fn enc = nullptr;
  if (!enc) {
    void* fn = nullptr;
    cudaDriverEntryPointQueryResult qr;
    cudaGetDriverEntryPoint("cuTensorMapEncodeTiled", &fn, cudaEnableDefault, &qr);
    enc = (enc_fn)fn;
    cudaFuncSetAttribute(main_kernel, cudaFuncAttributeMaxDynamicSharedMemorySize, SM_TOTAL);
  }
  CUtensorMap tm_x, tm_wqkv, tm_w1, tm_w2, tm_wo, tm_out;
  make_map(enc, &tm_out, d_out, D_, S_, 64, 128);
  make_map(enc, &tm_x, x, D_, S_, 64, 128);
  make_map(enc, &tm_wqkv, wqkv, 3 * D_, D_, 64, 96);
  make_map(enc, &tm_w1, w1, F_, D_, 64, 48);
  make_map(enc, &tm_w2, w2, D_, F_, 64, 48);
  make_map(enc, &tm_wo, wo, D_, D_, 64, 48);
  auto mk = [](uint32_t addr, uint32_t lbo, uint32_t sbo, uint32_t swz) {
    return ((uint64_t)desc_hi(sbo, swz) << 32) | (uint64_t)((addr >> 4) | desc_lbo(lbo));
  };
  Descs ds;
  ds.w = mk(SB0, 0, 1024, 1);
  ds.x = mk(SB0 + SM_RES, 0, 1024, 1);
  ds.h = mk(SB0 + SM_RES, 2048, 128, 0);
  ds.k0 = mk(SB0 + SM_KV, 2048, 128, 0);
  ds.kx = mk(SB0 + SM_KV + 8192, 0, 128, 0);
  ds.v = mk(SB0 + SM_KV + 4096, 128, 2048, 0);
  ds.dbg = 0; ds.sa = 0; ds.sb = 62; ds.sc = 52;
  main_kernel<<<NRT * NG + 4, 512, SM_TOTAL>>>(tm_x, tm_wqkv, tm_w1, tm_w2, tm_wo, tm_out, ds, x, b1, b2, (bf16*)d_out,
                                          (const uint8_t*)wqkv, (const uint8_t*)w1, (const uint8_t*)w2, (const uint8_t*)wo);
}
```
